```python
import torch

def _softmax(x, axis=-1):
    return torch.softmax(x, dim=axis)

def _gelu(x):
    return torch.nn.functional.gelu(x, approximate='tanh')

def _silu(x):
    return torch.nn.functional.silu(x)

def _sigmoid(x):
    return torch.sigmoid(x)

def _layernorm(x, axis=-1, eps=1e-05):
    m = x.mean(dim=axis, keepdim=True)
    v = x.var(dim=axis, keepdim=True, unbiased=False)
    return (x - m) / torch.sqrt(v + eps)

def _scatter_add(tgt, idx, src, axis=0):
    return tgt.clone().index_add_(axis, idx, src)

def _segment_sum(src, seg, n):
    out = torch.zeros((n,) + src.shape[1:], dtype=src.dtype)
    return out.index_add_(0, seg, src)

def _pad(x, pw):
    flat = tuple((v for pair in reversed(pw) for v in pair))
    return torch.nn.functional.pad(x, flat)
kernel_name = 'adaLN_cond__sliding_block_cached__glu_gated_swiglu__decode'

def setup_inputs():

    _w = lambda a: (lambda t: t.to(torch.bfloat16) if t.is_floating_point() else t)(torch.as_tensor(a))

    def _A_setup():
        B, Sq, D = (2, 1, 512)
        Hq, Hkv, Sk, Dh = (32, 32, 16384, 128)
        assert Hq % Hkv == 0, (Hq, Hkv)
        return {'x': _w((lambda *s: torch.randn(*s, dtype=torch.bfloat16) * 0.05)(B, Sq, D)), 'k_cache': _w((lambda *s: torch.randn(*s, dtype=torch.bfloat16) * 3.2)(B, Hkv, Sk, Dh)), 'v_cache': _w((lambda *s: torch.randn(*s, dtype=torch.bfloat16) * 3.2)(B, Hkv, Sk, Dh)), 'wq': _w((lambda *s: torch.randn(*s, dtype=torch.bfloat16) * 3.2)(D, Hq * Dh) * D ** (-0.5)), 'wo': _w((lambda *s: torch.randn(*s, dtype=torch.bfloat16) * 3.2)(Hq * Dh, D) * (Hq * Dh) ** (-0.5))}
    _A_in = _A_setup()

    def _B_setup():
        B, S, D, F = (2, 1, 512, 1376)
        return {'x': _w((lambda *s: torch.randn(*s, dtype=torch.bfloat16) * 0.05)(B, S, D)), 'w1': _w((lambda *s: torch.randn(*s, dtype=torch.bfloat16) * 1.6)(D, F) * (2.0 / D) ** 0.5), 'w3': _w((lambda *s: torch.randn(*s, dtype=torch.bfloat16) * 1.6)(D, F) * (2.0 / D) ** 0.5), 'w2': _w((lambda *s: torch.randn(*s, dtype=torch.bfloat16) * 1.6)(F, D) * (2.0 / F) ** 0.5)}
    _B_in = _B_setup()
    return {'A_x': _A_in['x'], 'A_k_cache': _A_in['k_cache'], 'A_v_cache': _A_in['v_cache'], 'A_wq': _A_in['wq'], 'A_wo': _A_in['wo'], 'B_x': _B_in['x'], 'B_w1': _B_in['w1'], 'B_w3': _B_in['w3'], 'B_w2': _B_in['w2'], 'c': _w((lambda *s: torch.randn(*s, dtype=torch.bfloat16) * 0.2)(2, 512) * 8.0), 'w_mod': _w((lambda *s: torch.randn(*s, dtype=torch.bfloat16) * 0.2)(512, 6 * 512) * 512 ** (-0.5) * 8.0)}

def reference(A_x, A_k_cache, A_v_cache, A_wq, A_wo, B_x, B_w1, B_w3, B_w2, c, w_mod):

    def _A_ref(x, k_cache, v_cache, wq, wo):
        B, Sq, D = x.shape
        Hq, Dh = (32, 128)
        Hkv, Sk = (k_cache.shape[1], k_cache.shape[2])
        W = min(4096, max(256, Sk // 4))
        rep = Hq // Hkv
        q = (lambda x, *d: x.permute(*d))((x @ wq).reshape(B, Sq, Hq, Dh), 0, 2, 1, 3)
        k = (lambda x, n, axis: torch.repeat_interleave(x, n, dim=axis))(k_cache[:, :, Sk - W:, :], rep, axis=1)
        v = (lambda x, n, axis: torch.repeat_interleave(x, n, dim=axis))(v_cache[:, :, Sk - W:, :], rep, axis=1)
        scores = torch.einsum('bhqd,bhkd->bhqk', q, k) * Dh ** (-0.5)
        p = _softmax(scores, axis=-1)
        o = torch.einsum('bhqk,bhkd->bhqd', p, v)
        return (lambda x, *d: x.permute(*d))(o, 0, 2, 1, 3).reshape(B, Sq, Hq * Dh) @ wo

    def _B_ref(x, w1, w3, w2):
        gate = torch.einsum('bsd,df->bsf', x, w1)
        up = torch.einsum('bsd,df->bsf', x, w3)
        h = _silu(gate) * up
        out = torch.einsum('bsf,fd->bsd', h, w2)
        return out
    x = A_x
    mod = (_silu(c) @ w_mod).reshape(c.shape[0], 6, 1, -1)
    sa, ca, ga, sb, cb, gb = (mod[:, 0].clone(), mod[:, 1].clone(), mod[:, 2].clone(), mod[:, 3].clone(), mod[:, 4].clone(), mod[:, 5].clone())
    h = _layernorm(x, axis=-1) * (1 + ca) + sa
    x = x + ga * _A_ref(h, A_k_cache, A_v_cache, A_wq, A_wo)
    h = _layernorm(x, axis=-1) * (1 + cb) + sb
    x = x + gb * _B_ref(h, B_w1, B_w3, B_w2)
    return x
```

```cpp
#include <cuda_runtime.h>
#include <cuda.h>
#include <cuda_bf16.h>
#include <stdint.h>

namespace {

typedef __nv_bfloat16 bf16;
typedef unsigned long long u64;

constexpr int DM   = 512;
constexpr int SK   = 16384;
constexpr int WIN  = 4096;
constexpr int FF   = 1376;
constexpr int NCTA = 128;
constexpr int NFFN = 86;
constexpr int NPP  = 88;
constexpr int NS   = 7;
constexpr int TILE = 16384;
#define BURST 5
#define NPF 3
#define FSTEADY 4
#define RELD 5
#define HDELAY 2400u
#define XDELAY 300u
#define J_WM 16
#define VD 7
#define VDEPTH 32
#define POLL_REM 0
#define TH_MUL 1
#define THETA 4
constexpr int NTHREADS = 320;

constexpr int SM_W    = 0;
constexpr int SM_RING = 65536;
constexpr int SM_SCO  = SM_RING + NS * TILE;
constexpr int SM_SCR  = SM_SCO + 16384;
constexpr int SM_P    = SM_SCR + 16384;
constexpr int SM_RMOD = SM_P + 8192;
constexpr int SM_RQ   = SM_RMOD + 512;
constexpr int SM_RO   = SM_RQ + 2048;
constexpr int SM_RGU  = SM_RO + 2048;
constexpr int SM_SILU = SM_RGU + 2048;
constexpr int SM_STAT = SM_SILU + 2048;
constexpr int SM_SMAX = SM_STAT + 128;
constexpr int SM_SSUM = SM_SMAX + 32;
constexpr int SM_SCNT = SM_SSUM + 32;
constexpr int SM_BAR  = SM_SCNT + 32;
constexpr int SM_END  = SM_BAR + 8 * (2 * NS + 11);
static_assert(VD * 2048 * 8 <= NS * TILE, "V rings");
constexpr int SMEM_BYTES = SM_END + 1024;
static_assert(SMEM_BYTES <= 232448, "smem");

__device__ unsigned int g_epoch;
__device__ __align__(128) u64 g_ll_x[2 * 256];
__device__ __align__(128) u64 g_ll_m[2 * 6 * 256];
__device__ __align__(128) uint32_t g_ll_r[2 * 32 * NPP * 32];
#define TSTAMP(i) do { } while (0)
#define TSTAMPD(i, dep) do { } while (0)

__device__ __forceinline__ uint32_t smem_u32(const void* p) { return (uint32_t)__cvta_generic_to_shared(p); }
__device__ __forceinline__ uint32_t pack_bf16(float lo, float hi) {
    uint32_t r; asm("cvt.rn.bf16x2.f32 %0, %1, %2;" : "=r"(r) : "f"(hi), "f"(lo)); return r;
}
__device__ __forceinline__ float bf16r(float v) { return __uint_as_float(pack_bf16(0.0f, v)); }
__device__ __forceinline__ float bf_lo(uint32_t v) { return __uint_as_float(v << 16); }
__device__ __forceinline__ float bf_hi(uint32_t v) { return __uint_as_float(v & 0xffff0000u); }
__device__ __forceinline__ uint32_t bf2_mul(uint32_t a, uint32_t b) { uint32_t r; asm("mul.rn.bf16x2 %0, %1, %2;" : "=r"(r) : "r"(a), "r"(b)); return r; }
__device__ __forceinline__ uint32_t bf2_add(uint32_t a, uint32_t b) { uint32_t r; asm("add.rn.bf16x2 %0, %1, %2;" : "=r"(r) : "r"(a), "r"(b)); return r; }
__device__ __forceinline__ uint32_t bf2_sub(uint32_t a, uint32_t b) { uint32_t r; asm("sub.rn.bf16x2 %0, %1, %2;" : "=r"(r) : "r"(a), "r"(b)); return r; }
__device__ __forceinline__ float ex2_fast(float v) { float r; asm("ex2.approx.ftz.f32 %0, %1;" : "=f"(r) : "f"(v)); return r; }
__device__ __forceinline__ float ex2_sub(float v) { float r; asm("ex2.approx.f32 %0, %1;" : "=f"(r) : "f"(v)); return r; }
__device__ __forceinline__ float sqrt_fast(float v) { float r; asm("sqrt.approx.ftz.f32 %0, %1;" : "=f"(r) : "f"(v)); return r; }
__device__ __forceinline__ float rcp_fast(float v) { float r; asm("rcp.approx.ftz.f32 %0, %1;" : "=f"(r) : "f"(v)); return r; }
constexpr float LOG2E = 1.4426950408889634f;
__device__ __forceinline__ float silu_f(float v) { return v * rcp_fast(1.0f + ex2_fast(-LOG2E * v)); }
__device__ __forceinline__ float ln_rden(float var) { return rcp_fast(bf16r(sqrt_fast(bf16r(bf16r(var) + 1e-5f)))); }
__device__ __forceinline__ uint32_t ln_pair(uint32_t x2, uint32_t m2, float rden) {
    const uint32_t d = bf2_sub(x2, m2);
    return pack_bf16(bf_lo(d) * rden, bf_hi(d) * rden);
}

__device__ __forceinline__ void mbar_init(uint32_t bar, uint32_t cnt) {
    asm volatile("mbarrier.init.shared::cta.b64 [%0], %1;" :: "r"(bar), "r"(cnt) : "memory");
}
__device__ __forceinline__ void mbar_expect_tx(uint32_t bar, uint32_t bytes) {
    asm volatile("mbarrier.arrive.expect_tx.shared::cta.b64 _, [%0], %1;" :: "r"(bar), "r"(bytes) : "memory");
}
__device__ __forceinline__ void mbar_arrive(uint32_t bar) {
    asm volatile("mbarrier.arrive.shared::cta.b64 _, [%0];" :: "r"(bar) : "memory");
}
__device__ __forceinline__ uint32_t clk32() { uint32_t c; asm volatile("mov.u32 %0, %%clock;" : "=r"(c)); return c; }
__device__ __forceinline__ void check_timeout(uint32_t t0) { if ((int32_t)(clk32() - t0) < 0) __trap(); }
#define MBAR_WAIT_ASM(SEM) \
    asm volatile("{\n.reg .pred p;\n.reg .s32 t1;\n" \
                 "W_%=:\n" \
                 "mbarrier.try_wait.parity" SEM ".shared::cta.b64 p, [%0], %1;\n@p bra D_%=;\n" \
                 "mov.u32 t1, %%clock;\nsub.s32 t1, t1, %2;\nsetp.ge.s32 p, t1, 0;\n@p bra W_%=;\ntrap;\n" \
                 "D_%=:\n}" :: "r"(bar), "r"(parity), "r"(t0) : "memory")
__device__ __forceinline__ void mbar_wait_t(uint32_t bar, uint32_t parity, uint32_t t0) { MBAR_WAIT_ASM(""); }
__device__ __forceinline__ void mbar_wait_cluster_t(uint32_t bar, uint32_t parity, uint32_t t0) { MBAR_WAIT_ASM(".acquire.cluster"); }
#define mbar_wait(bar, parity) mbar_wait_t(bar, parity, t0)
#define mbar_wait_cluster(bar, parity) mbar_wait_cluster_t(bar, parity, t0)
__device__ __forceinline__ bool mbar_test(uint32_t bar, uint32_t parity) {
    uint32_t ok;
    asm volatile("{\n.reg .pred p;\nmbarrier.test_wait.parity.shared::cta.b64 p, [%1], %2;\nselp.u32 %0, 1, 0, p;\n}"
                 : "=r"(ok) : "r"(bar), "r"(parity) : "memory");
    return ok != 0;
}
__device__ __forceinline__ bool elect_one() {
    uint32_t p;
    asm volatile("{\n.reg .pred P;\nelect.sync _|P, 0xffffffff;\nselp.u32 %0, 1, 0, P;\n}" : "=r"(p));
    return p != 0;
}
__device__ __forceinline__ void tma2d(uint32_t dst, const CUtensorMap* tm, int c0, int c1, uint32_t bar) {
    asm volatile("cp.async.bulk.tensor.2d.shared::cluster.global.mbarrier::complete_tx::bytes [%0], [%1, {%3, %4}], [%2];"
                 :: "r"(dst), "l"(tm), "r"(bar), "r"(c0), "r"(c1) : "memory");
}
__device__ __forceinline__ void tma2d_ef(uint32_t dst, const CUtensorMap* tm, int c0, int c1, uint32_t bar, u64 pol) {
    asm volatile("cp.async.bulk.tensor.2d.shared::cluster.global.mbarrier::complete_tx::bytes.L2::cache_hint [%0], [%1, {%3, %4}], [%2], %5;"
                 :: "r"(dst), "l"(tm), "r"(bar), "r"(c0), "r"(c1), "l"(pol) : "memory");
}
__device__ __forceinline__ void ldsm2t(uint32_t& a0, uint32_t& a1, uint32_t addr) {
    asm volatile("ldmatrix.sync.aligned.m8n8.x2.trans.shared.b16 {%0,%1}, [%2];" : "=r"(a0), "=r"(a1) : "r"(addr) : "memory");
}
__device__ __forceinline__ void ldsm4(uint32_t (&a)[4], uint32_t addr) {
    asm volatile("ldmatrix.sync.aligned.m8n8.x4.shared.b16 {%0,%1,%2,%3}, [%4];"
                 : "=r"(a[0]), "=r"(a[1]), "=r"(a[2]), "=r"(a[3]) : "r"(addr) : "memory");
}
__device__ __forceinline__ void ldsm4t(uint32_t (&a)[4], uint32_t addr) {
    asm volatile("ldmatrix.sync.aligned.m8n8.x4.trans.shared.b16 {%0,%1,%2,%3}, [%4];"
                 : "=r"(a[0]), "=r"(a[1]), "=r"(a[2]), "=r"(a[3]) : "r"(addr) : "memory");
}
__device__ __forceinline__ void mma16816(float (&d)[4], const uint32_t (&a)[4], uint32_t b0, uint32_t b1) {
    asm volatile("mma.sync.aligned.m16n8k16.row.col.f32.bf16.bf16.f32 {%0,%1,%2,%3}, {%4,%5,%6,%7}, {%8,%9}, {%0,%1,%2,%3};"
                 : "+f"(d[0]), "+f"(d[1]), "+f"(d[2]), "+f"(d[3])
                 : "r"(a[0]), "r"(a[1]), "r"(a[2]), "r"(a[3]), "r"(b0), "r"(b1));
}
__device__ __forceinline__ void mma16816z(float (&d)[4], const uint32_t (&a)[4], uint32_t b0, uint32_t b1) {
    asm volatile("mma.sync.aligned.m16n8k16.row.col.f32.bf16.bf16.f32 {%0,%1,%2,%3}, {%4,%5,%6,%7}, {%8,%9}, {%10,%10,%10,%10};"
                 : "=f"(d[0]), "=f"(d[1]), "=f"(d[2]), "=f"(d[3])
                 : "r"(a[0]), "r"(a[1]), "r"(a[2]), "r"(a[3]), "r"(b0), "r"(b1), "f"(0.0f));
}
template <int ID, int N> __device__ __forceinline__ void bar_sync() { asm volatile("bar.sync %0, %1;" :: "n"(ID), "n"(N) : "memory"); }
template <int ID, int N> __device__ __forceinline__ void bar_arrive() { asm volatile("bar.arrive %0, %1;" :: "n"(ID), "n"(N) : "memory"); }
__device__ __forceinline__ void cluster_arrive_relaxed() { asm volatile("barrier.cluster.arrive.relaxed.aligned;" ::: "memory"); }
__device__ __forceinline__ void cluster_wait() { asm volatile("barrier.cluster.wait.acquire.aligned;" ::: "memory"); }

__device__ __forceinline__ void sts32f(uint32_t a, float v) { asm volatile("st.shared.f32 [%0], %1;" :: "r"(a), "f"(v) : "memory"); }
__device__ __forceinline__ void sts32(uint32_t a, uint32_t v) { asm volatile("st.shared.b32 [%0], %1;" :: "r"(a), "r"(v) : "memory"); }
__device__ __forceinline__ uint32_t lds32(uint32_t a) { uint32_t v; asm volatile("ld.shared.b32 %0, [%1];" : "=r"(v) : "r"(a) : "memory"); return v; }
__device__ __forceinline__ float2 lds64f(uint32_t a) { float2 v; asm volatile("ld.shared.v2.f32 {%0,%1}, [%2];" : "=f"(v.x), "=f"(v.y) : "r"(a) : "memory"); return v; }
__device__ __forceinline__ float4 lds128f(uint32_t a) { float4 v; asm volatile("ld.shared.v4.f32 {%0,%1,%2,%3}, [%4];" : "=f"(v.x), "=f"(v.y), "=f"(v.z), "=f"(v.w) : "r"(a) : "memory"); return v; }
__device__ __forceinline__ void lds64(uint32_t& x, uint32_t& y, uint32_t a) { asm volatile("ld.shared.v2.b32 {%0,%1}, [%2];" : "=r"(x), "=r"(y) : "r"(a) : "memory"); }
__device__ __forceinline__ void lds128(uint32_t* v, uint32_t a) { asm volatile("ld.shared.v4.b32 {%0,%1,%2,%3}, [%4];" : "=r"(v[0]), "=r"(v[1]), "=r"(v[2]), "=r"(v[3]) : "r"(a) : "memory"); }
__device__ __forceinline__ void sts64f(uint32_t a, float x, float y) { asm volatile("st.shared.v2.f32 [%0], {%1,%2};" :: "r"(a), "f"(x), "f"(y) : "memory"); }
__device__ __forceinline__ void sts64(uint32_t a, uint32_t x, uint32_t y) { asm volatile("st.shared.v2.b32 [%0], {%1,%2};" :: "r"(a), "r"(x), "r"(y) : "memory"); }
__device__ __forceinline__ void sts128(uint32_t a, uint32_t x, uint32_t y, uint32_t z, uint32_t w) { asm volatile("st.shared.v4.b32 [%0], {%1,%2,%3,%4};" :: "r"(a), "r"(x), "r"(y), "r"(z), "r"(w) : "memory"); }
__device__ __forceinline__ void sts128f(uint32_t a, float x, float y, float z, float w) { asm volatile("st.shared.v4.f32 [%0], {%1,%2,%3,%4};" :: "r"(a), "f"(x), "f"(y), "f"(z), "f"(w) : "memory"); }

__device__ __forceinline__ void ll_st(u64* p, uint32_t lo, uint32_t hi) {
    asm volatile("{\n.reg .b64 v;\nmov.b64 v, {%1, %2};\nst.relaxed.gpu.global.b64 [%0], v;\n}" :: "l"(p), "r"(lo), "r"(hi) : "memory");
}
__device__ __forceinline__ void ll_ld2(const u64* p, uint4& v) {
    asm volatile("{\n.reg .b64 a, b;\nld.relaxed.gpu.global.v2.b64 {a, b}, [%4];\nmov.b64 {%0, %1}, a;\nmov.b64 {%2, %3}, b;\n}"
                 : "=r"(v.x), "=r"(v.y), "=r"(v.z), "=r"(v.w) : "l"(p) : "memory");
}
__device__ __forceinline__ void ll_poll2(const u64* p, uint4& v, uint32_t flag, uint32_t t0) {
    while (!__all_sync(0xffffffffu, v.y == flag && v.w == flag)) { ll_ld2(p, v); check_timeout(t0); }
}
__device__ __forceinline__ void tag_st(uint32_t* p, float v, uint32_t tag) {
    asm volatile("st.relaxed.gpu.global.u32 [%0], %1;" :: "l"(p), "r"((__float_as_uint(v) & ~3u) | tag) : "memory");
}
__device__ __forceinline__ float sel4(int t, float a, float b, float c, float d) {
    float lo = (t & 1) ? b : a, hi = (t & 1) ? d : c;
    return (t & 2) ? hi : lo;
}

struct Maps { CUtensorMap K, V, Wq, Wo, W2, Wm, W1, W3, Wm16; };

__global__ void __cluster_dims__(2, 1, 1) __launch_bounds__(NTHREADS, 1)
fused_decode_kernel(const bf16* __restrict__ x, const bf16* __restrict__ cvec, const bf16* __restrict__ vcache,
                    bf16* __restrict__ out, const __grid_constant__ Maps tm)
{
    extern __shared__ uint8_t smem_raw[];
    const uint32_t sb = (smem_u32(smem_raw) + 1023u) & ~1023u;
    const int tid = threadIdx.x, lane = tid & 31;
    const int warp = __shfl_sync(0xffffffffu, tid >> 5, 0);
    const uint32_t t0 = clk32();
    const int r = blockIdx.x;
    const int half = r & 1, b = r >> 6, cg = r & 63;
    const int g = lane >> 2, t = lane & 3;
    const uint32_t bar_w = sb + SM_BAR, bar_full = bar_w + 32, bar_sc = bar_full + 8 * NS;
    const uint32_t bar_f = bar_sc + 8, bar_m = bar_f + 8, bar_wfree = bar_m + 8, bar_go = bar_wfree + 8, bar_empty = bar_go + 8;
    const uint32_t bar_f2 = bar_empty + 8 * NS, bar_wfree2 = bar_f2 + 8;
    const bool is_ffn = r < NFFN;
    const uint32_t l_row = (lane & 7) + 8 * (lane >> 4);
    const uint32_t l_sel = (lane >> 3) & 1;

    if (warp == 8) {
        const bool el = elect_one();
        const int kv_row0 = (r >> 1) * SK + (SK - WIN);
        u64 pol;
        asm volatile("createpolicy.fractional.L2::evict_first.b64 %0, 1.0;" : "=l"(pol));
        if (el) {
            TSTAMP(0);
            mbar_init(bar_m, 1);
#pragma unroll
            for (int i = 0; i < BURST; i++) mbar_init(bar_w + 8 * i, 1);
            asm volatile("fence.mbarrier_init.release.cluster;" ::: "memory");
            mbar_expect_tx(bar_m, 8192);
            tma2d(sb + SM_P, &tm.Wm, r * 8, 0, bar_m);
            tma2d(sb + SM_P + 4096, &tm.Wm, r * 8, 256, bar_m);
#pragma unroll
            for (int i = 0; i < BURST; i++) {
                mbar_expect_tx(bar_w + 8 * i, TILE);
                if (i < 4) tma2d(sb + i * TILE, &tm.Wq, cg * 64, i * 128, bar_w + 8 * i);
                else       tma2d_ef(sb + i * TILE, &tm.K, half * 64, kv_row0 + (i - 4) * 128, bar_w + 8 * i, pol);
            }
            TSTAMP(8);
#pragma unroll
            for (int i = BURST; i < 2 * NS + 11; i++) if (i != NS + 6) mbar_init(bar_w + 8 * i, (i < NS + 9 || i == 2 * NS + 9) ? 1 : 8);
            asm volatile("fence.mbarrier_init.release.cluster;" ::: "memory");
            mbar_expect_tx(bar_sc, 16384);
        }
        __syncwarp();
        cluster_arrive_relaxed();
#pragma unroll 1
        for (int u = BURST; u < 4 + NS + NPF; u++) {
            const uint32_t gb = bar_w + 8 * (u >= BURST + 2 ? u - (BURST - 2) : 2 * (u - BURST) + 1);
            bool rel;
            while (!((rel = mbar_test(bar_empty, 0)) && (u >= 4 + NS || mbar_test(bar_w + 8 * (u - RELD), 0))) && !mbar_test(gb, 0)) check_timeout(t0);
            if (u < 4 + NS) {
                if (el) {
                    mbar_expect_tx(bar_w + 8 * u, TILE);
                    tma2d_ef(sb + u * TILE, &tm.K, half * 64, kv_row0 + (u - 4) * 128, bar_w + 8 * u, pol);
                }
            } else {
                if (rel) break;
                if (el) asm volatile("cp.async.bulk.prefetch.tensor.2d.L2.global.tile [%0, {%1, %2}];"
                                     :: "l"(&tm.K), "r"(half * 64), "r"(kv_row0 + (u - 4) * 128) : "memory");
            }
        }
        if (el) TSTAMP(16);
        int slot = 0, gslot = NS - FSTEADY;
        uint32_t ph = 0, gph = 0;
#pragma unroll 1
        for (int j = NS; j < 36; j++) {
            if (j == J_WM && el) {
                mbar_expect_tx(bar_m, 16384);
                tma2d(sb + SM_W, &tm.Wm16, 2 * DM + r * 16, 0, bar_m);
                tma2d(sb + SM_W + 8192, &tm.Wm16, 2 * DM + r * 16, 256, bar_m);
            }
            if (j < 32) mbar_wait(bar_empty + 8 * slot, ph);
            else if (j == 32) mbar_wait(bar_wfree, 0);
            if (FSTEADY < NS) {
                mbar_wait(bar_full + 8 * gslot, gph);
                if (++gslot == NS) { gslot = 0; gph ^= 1u; }
            }
            if (j < 32) {
                if (el) {
                    mbar_expect_tx(bar_full + 8 * slot, TILE);
                    tma2d_ef(sb + SM_RING + slot * TILE, &tm.K, half * 64, kv_row0 + j * 128, bar_full + 8 * slot, pol);
                }
                if (++slot == NS) { slot = 0; ph ^= 1u; }
            } else if (el) {
                const int i = 2 * (j - 32);
                mbar_expect_tx(bar_w + 4 * i, TILE);
                tma2d(sb + SM_W + i * 8192, &tm.Wo, i * 64, cg * 64, bar_w + 4 * i);
                tma2d(sb + SM_W + i * 8192 + 8192, &tm.Wo, i * 64 + 64, cg * 64, bar_w + 4 * i);
            }
        }
        if (el) TSTAMP(17);
        if (is_ffn) {
            mbar_wait(bar_go, 0);
            mbar_wait(bar_wfree2, 0);
            if (el) TSTAMP(18);
            if (el) {
                mbar_expect_tx(bar_f, 32768);
#pragma unroll 1
                for (int i = 0; i < 4; i++) tma2d(sb + SM_W + i * 8192, i < 2 ? &tm.W1 : &tm.W3, r * 16, (i & 1) * 256, bar_f);
                mbar_expect_tx(bar_f2, TILE);
#pragma unroll 1
                for (int i = 0; i < 8; i++) tma2d(sb + SM_W + 32768 + i * 2048, &tm.W2, i * 64, r * 16, bar_f2);
            }
        }
        cluster_wait();
        return;
    }

    uint32_t flag;
    asm volatile("ld.relaxed.gpu.global.u32 %0, [%1];" : "=r"(flag) : "l"(&g_epoch) : "memory");

    if (warp == 9) {
        const uint4* xp = reinterpret_cast<const uint4*>(x + b * DM);
        const uint4 xa = __ldg(xp + lane), xb = __ldg(xp + 32 + lane);
        cluster_arrive_relaxed();
        flag += 1u;
        const uint32_t xw[8] = {xa.x, xa.y, xa.z, xa.w, xb.x, xb.y, xb.z, xb.w};
        float s = 0.f;
#pragma unroll
        for (int i = 0; i < 8; i++) s += bf_lo(xw[i]) + bf_hi(xw[i]);
#pragma unroll 1
        for (int o = 16; o > 0; o >>= 1) s += __shfl_xor_sync(0xffffffffu, s, o);
        const float mean = s * (1.0f / DM);
        float m2 = 0.f;
#pragma unroll
        for (int i = 0; i < 8; i++) { const float d0 = bf_lo(xw[i]) - mean, d1 = bf_hi(xw[i]) - mean; m2 += d0 * d0; m2 += d1 * d1; }
#pragma unroll 1
        for (int o = 16; o > 0; o >>= 1) m2 += __shfl_xor_sync(0xffffffffu, m2, o);
        {
            const uint32_t mm = pack_bf16(mean, mean);
            const float rden = ln_rden(m2 * (1.0f / DM));
            sts128(sb + SM_RO + lane * 16, ln_pair(xa.x, mm, rden), ln_pair(xa.y, mm, rden), ln_pair(xa.z, mm, rden), ln_pair(xa.w, mm, rden));
            sts128(sb + SM_RO + 512 + lane * 16, ln_pair(xb.x, mm, rden), ln_pair(xb.y, mm, rden), ln_pair(xb.z, mm, rden), ln_pair(xb.w, mm, rden));
        }
        const int fpos = (cg >> 1) * 8 + 2 * t + (cg & 1);
        if (lane == 0) TSTAMP(19);
        bar_sync<2, 288>();
        {
            float4 v = lds128f(sb + SM_RMOD + g * 64 + t * 16);
#pragma unroll
            for (int o = 4; o < 32; o <<= 1) {
                v.x += __shfl_xor_sync(0xffffffffu, v.x, o); v.y += __shfl_xor_sync(0xffffffffu, v.y, o);
                v.z += __shfl_xor_sync(0xffffffffu, v.z, o); v.w += __shfl_xor_sync(0xffffffffu, v.w, o);
            }
            uint32_t m = g ? pack_bf16(v.y, v.w) : pack_bf16(v.x, v.z);
            if (b) m = bf2_add(m, 0x3f803f80u);
            if (lane < 8) ll_st(&g_ll_m[(g * 6 + b) * 256 + fpos], m, flag);
        }
        if (lane == 0) TSTAMP(1);
        cluster_wait();

        {
            float d[2][4];
#pragma unroll
            for (int i = 0; i < 4; i++) { d[0][i] = d[1][i] = 0.f; }
            mbar_wait(bar_m, 1);
            const uint32_t base = sb + SM_W + l_row * 32 + ((l_sel ^ (g & 1)) << 4);
            const uint32_t sa = sb + SM_SILU + (g & 1) * 1024 + t * 4;
#pragma unroll 1
            for (int ks = 0; ks < 32; ks += 2) {
                uint32_t a0[4], a1[4];
                ldsm4t(a0, base + ks * 512);
                ldsm4t(a1, base + ks * 512 + 512);
                mma16816(d[0], a0, lds32(sa + ks * 32), lds32(sa + ks * 32 + 16));
                mma16816(d[1], a1, lds32(sa + ks * 32 + 32), lds32(sa + ks * 32 + 48));
            }
            if (lane == 0) mbar_arrive(bar_wfree);
            const uint32_t p0 = pack_bf16(d[0][0] + d[1][0], d[0][2] + d[1][2]), p1 = pack_bf16(d[0][1] + d[1][1], d[0][3] + d[1][3]);
            const uint32_t a0 = __shfl_sync(0xffffffffu, p0, 8 * t), a1 = __shfl_sync(0xffffffffu, p0, 8 * t + 4);
            const uint32_t c0 = __shfl_sync(0xffffffffu, p1, 8 * t), c1 = __shfl_sync(0xffffffffu, p1, 8 * t + 4);
            uint32_t m = __byte_perm((g & 2) ? c0 : a0, (g & 2) ? c1 : a1, (g & 1) ? 0x7632 : 0x5410);
            if ((r >> 5) == 2) m = bf2_add(m, 0x3f803f80u);
            if (lane < 16) ll_st(&g_ll_m[((g >> 1) * 6 + 2) * 256 + r * 8 + 2 * t + (g & 1)], m, flag);
            if (lane == 0) TSTAMP(13);
        }

        bar_sync<4, 288>();
        if (is_ffn) {
            const uint32_t* base = g_ll_r + ((r & 31) * NPP + lane) * 32;
            while (true) {
                uint32_t v0, v1;
                asm volatile("ld.relaxed.gpu.global.u32 %0, [%1];" : "=r"(v0) : "l"(base) : "memory");
                asm volatile("ld.relaxed.gpu.global.u32 %0, [%1];" : "=r"(v1) : "l"(base + 1024) : "memory");
                const int cnt = __popc(__ballot_sync(0xffffffffu, ((v0 ^ flag) & 3u) == 0)) + __popc(__ballot_sync(0xffffffffu, ((v1 ^ flag) & 3u) == 0));
                if (cnt >= THETA + TH_MUL * ((r >> 1) & 7)) break;
                __nanosleep(200);
                check_timeout(t0);
            }
            if (lane == 0) mbar_arrive(bar_go);
        }
        if (r >= 32 && r < 96) return;
        const bool fin = r < 32;
        const int fb = fin ? (lane >> 3) & 1 : (r >> 4) & 1;
        const int col = fin ? r * 16 + (lane >> 4) * 8 + (lane & 7) : (r & 15) * 32 + lane;
        const int wi = (col >> 4) * 8 + (col & 6) + ((col >> 3) & 1);
        u64 gw, xq;
        while (true) {
            asm volatile("ld.relaxed.gpu.global.b64 %0, [%1];" : "=l"(gw) : "l"(&g_ll_m[(fb * 6 + (fin ? 5 : 2)) * 256 + wi]) : "memory");
            if (__all_sync(0xffffffffu, (uint32_t)(gw >> 32) == flag)) break;
            check_timeout(t0);
        }
        if (fin) {
            bar_sync<7, 288>();
            while (true) {
                asm volatile("ld.relaxed.gpu.global.b64 %0, [%1];" : "=l"(xq) : "l"(&g_ll_x[fb * 256 + wi]) : "memory");
                if (__all_sync(0xffffffffu, (uint32_t)(xq >> 32) == flag)) break;
                check_timeout(t0);
            }
        } else {
            xq = __ldg(reinterpret_cast<const uint32_t*>(x + fb * DM) + (col >> 1));
        }
        const float xin = (lane & 1) ? bf_hi((uint32_t)xq) : bf_lo((uint32_t)xq);
        const float gt = (lane & 1) ? bf_hi((uint32_t)gw) : bf_lo((uint32_t)gw);
        sts32f(sb + SM_RMOD + lane * 4, xin + gt);
        bar_sync<6, 288>();
        float v[8];
#pragma unroll
        for (int i = 0; i < 8; i++) v[i] = __uint_as_float(lds32(sb + SM_RQ + i * 128 + lane * 4));
        const float res = xin + bf16r(gt * bf16r(((v[0] + v[1]) + (v[2] + v[3])) + ((v[4] + v[5]) + (v[6] + v[7]))));
        const uint32_t pr = pack_bf16(res, __shfl_down_sync(0xffffffffu, res, 1));
        if (!(lane & 1)) {
            if (fin) reinterpret_cast<uint32_t*>(out)[(fb * DM + col) >> 1] = pr;
            else ll_st(&g_ll_x[fb * 256 + wi], pr, flag);
        }
        TSTAMPD(fin ? 12 : 14, pr);
        if (r == 0 && lane == 0) asm volatile("st.relaxed.gpu.global.u32 [%0], %1;" :: "l"(&g_epoch), "r"(flag) : "memory");
        return;
    }

    const int w = warp;
    {
        const uint32_t* cp = reinterpret_cast<const uint32_t*>(cvec + 64 * w) + lane;
        const uint32_t c0 = __ldg(cp), c1 = __ldg(cp + DM / 2);
        cluster_arrive_relaxed();
        sts32(sb + SM_SILU + w * 128 + lane * 4, pack_bf16(silu_f(bf_lo(c0)), silu_f(bf_hi(c0))));
        sts32(sb + SM_SILU + 1024 + w * 128 + lane * 4, pack_bf16(silu_f(bf_lo(c1)), silu_f(bf_hi(c1))));
        cluster_wait();
        __syncwarp();
        uint32_t sc[8];
#pragma unroll
        for (int i = 0; i < 8; i++) sc[i] = lds32(sb + SM_SILU + (g & 1) * 1024 + w * 128 + i * 16 + t * 4);
        mbar_wait(bar_m, 0);
        if (tid == 0) TSTAMP(15);
        float d[2][4];
        uint32_t a[4][4];
#pragma unroll
        for (int ks = 0; ks < 4; ks++) {
            ldsm2t(a[ks][0], a[ks][2], sb + SM_P + (64 * w + 16 * ks + (lane & 15)) * 16);
            a[ks][1] = a[ks][3] = 0u;
        }
        mma16816z(d[0], a[0], sc[0], sc[1]); mma16816z(d[1], a[1], sc[2], sc[3]);
        mma16816(d[0], a[2], sc[4], sc[5]);  mma16816(d[1], a[3], sc[6], sc[7]);
        if (t == 0) sts64f(sb + SM_RMOD + w * 64 + g * 8, d[0][0] + d[1][0], d[0][1] + d[1][1]);
        bar_sync<2, 288>();
    }
    flag += 1u;

    const uint32_t tr_off = l_row * 128 + ((l_sel ^ (lane & 7)) << 4);
    const uint32_t red_st = (w * 64 + 16 * t + g) * 4;
    uint32_t qf[8];
    {
        const uint32_t lnp = sb + SM_RO + (32 * w + 8 * ((lane >> 2) & 3) + t) * 4;
        const uint32_t ln0 = lds32(lnp), ln1 = lds32(lnp + 16);
        uint4 hv; hv.y = ~flag;
        { const uint32_t c = clk32(); while (clk32() - c < HDELAY) ; }
        ll_poll2(g_ll_m + (b * 6 + (lane >> 4)) * 256 + 32 * w + 2 * (lane & 15), hv, flag, t0);
        uint32_t a[4][4][4];
        mbar_wait(bar_w + 8 * (w >> 1), 0);
        const uint32_t base = sb + SM_W + w * 8192 + tr_off;
#pragma unroll
        for (int j = 0; j < 4; j++)
#pragma unroll
            for (int ks = 0; ks < 4; ks++) ldsm4t(a[ks][j], (base ^ (j << 5)) + ks * 2048);
        if (tid == 0) TSTAMP(2);
        hv.x = bf2_add(bf2_mul(ln0, __shfl_down_sync(0xffffffffu, hv.x, 16)), hv.x);
        hv.z = bf2_add(bf2_mul(ln1, __shfl_down_sync(0xffffffffu, hv.z, 16)), hv.z);
        float d[4][4];
#pragma unroll
        for (int ks = 0; ks < 4; ks++) {
            const uint32_t b0 = __shfl_sync(0xffffffffu, hv.x, 4 * ks + t);
            const uint32_t b1 = __shfl_sync(0xffffffffu, hv.z, 4 * ks + t);
#pragma unroll
            for (int j = 0; j < 4; j++) { if (ks == 0) mma16816z(d[j], a[ks][j], b0, b1); else mma16816(d[j], a[ks][j], b0, b1); }
        }
        sts32f(sb + SM_RQ + red_st, sel4(t, d[0][0], d[1][0], d[2][0], d[3][0]));
        sts32f(sb + SM_RQ + red_st + 32, sel4(t, d[0][2], d[1][2], d[2][2], d[3][2]));
        bar_sync<1, 256>();
        float q0 = 0.f, q1 = 0.f;
#pragma unroll
        for (int i = 0; i < 8; i++) { float2 v = lds64f(sb + SM_RQ + i * 256 + lane * 8); q0 += v.x; q1 += v.y; }
        const uint32_t qp = pack_bf16(q0, q1);
#pragma unroll
        for (int i = 0; i < 8; i++) qf[i] = __shfl_sync(0xffffffffu, qp, 4 * i + t);
        if (tid == 0) TSTAMP(3);
    }

    int slot = 0;
    uint32_t ph = 0;
    {
        const uint32_t k_off = sb + SM_RING + (16 * w + (lane & 7) + 8 * l_sel) * 128 + (((lane >> 4) ^ (lane & 7)) << 4);
        uint32_t rem_sc, rem_bar;
        asm("mapa.shared::cluster.u32 %0, %1, %2;" : "=r"(rem_sc) : "r"(sb + SM_SCR), "r"(half ^ 1));
        asm("mapa.shared::cluster.u32 %0, %1, %2;" : "=r"(rem_bar) : "r"(bar_sc), "r"(half ^ 1));
        const uint32_t s_off = (16 * w + 8 * (t & 1) + g) * 4;
#pragma unroll 1
        for (int kt = 0; kt < 32; kt++) {
            mbar_wait(bar_full + 8 * slot, ph);
            const uint32_t base = k_off + slot * TILE;
            uint32_t a[4][4];
#pragma unroll
            for (int ks = 0; ks < 4; ks++) ldsm4(a[ks], base ^ (ks << 5));
            float d0[4], d1[4];
            mma16816z(d0, a[0], qf[0], qf[1]); mma16816z(d1, a[1], qf[2], qf[3]);
            mma16816(d0, a[2], qf[4], qf[5]); mma16816(d1, a[3], qf[6], qf[7]);
            if (lane == 0) mbar_arrive(bar_empty + 8 * slot);
            const float v = (t & 1) ? d0[2] + d1[2] : d0[0] + d1[0];
            if (t < 2) sts32f(sb + SM_SCO + kt * 512 + s_off, v);
            else asm volatile("st.async.weak.shared::cluster.mbarrier::complete_tx::bytes.f32 [%0], %1, [%2];"
                              :: "r"(rem_sc + kt * 512 + s_off), "f"(v), "r"(rem_bar) : "memory");
            if (++slot == NS) { slot = 0; ph ^= 1; }
        }
    }
    if (tid == 0) TSTAMP(4);
    int nrows;
    {
        bar_sync<1, 256>();
        mbar_wait_cluster(bar_sc, 0);
        const uint32_t sa = sb + SM_SCO + tid * 16;
        float u[4][4];
        float mx = -INFINITY;
#pragma unroll
        for (int j = 0; j < 4; j++) {
            const float4 p = lds128f(sa + j * 4096), v = lds128f(sa + j * 4096 + 16384);
            u[j][0] = bf16r(bf16r(p.x + v.x) * 0.08838834764831845f); u[j][1] = bf16r(bf16r(p.y + v.y) * 0.08838834764831845f);
            u[j][2] = bf16r(bf16r(p.z + v.z) * 0.08838834764831845f); u[j][3] = bf16r(bf16r(p.w + v.w) * 0.08838834764831845f);
            mx = fmaxf(fmaxf(mx, fmaxf(u[j][0], u[j][1])), fmaxf(u[j][2], u[j][3]));
        }
#pragma unroll
        for (int o = 16; o > 0; o >>= 1) mx = fmaxf(mx, __shfl_xor_sync(0xffffffffu, mx, o));
        if (lane == 0) sts32f(sb + SM_SMAX + w * 4, mx);
        bar_sync<1, 256>();
        {
            const float4 p = lds128f(sb + SM_SMAX), v = lds128f(sb + SM_SMAX + 16);
            mx = fmaxf(fmaxf(fmaxf(p.x, p.y), fmaxf(p.z, p.w)), fmaxf(fmaxf(v.x, v.y), fmaxf(v.z, v.w)));
        }
        float sum = 0.f;
        uint32_t keep = 0, cnt = 0;
#pragma unroll
        for (int j = 0; j < 4; j++) {
#pragma unroll
            for (int e = 0; e < 4; e++) {
                const float xx = (u[j][e] - mx) * LOG2E;
                if (!(xx < -134.0625f)) { keep |= 1u << (4 * j + e); cnt += 1u << (8 * j); }
                u[j][e] = ex2_sub(xx);
            }
            sum += (u[j][0] + u[j][1]) + (u[j][2] + u[j][3]);
        }
        uint32_t inc = cnt;
#pragma unroll
        for (int o = 1; o < 32; o <<= 1) {
            const uint32_t v = __shfl_up_sync(0xffffffffu, inc, o);
            if (lane >= o) inc += v;
            sum += __shfl_xor_sync(0xffffffffu, sum, o);
        }
        if (lane == 31) { sts32f(sb + SM_SSUM + w * 4, sum); sts32(sb + SM_SCNT + w * 4, inc); }
        bar_sync<1, 256>();
        {
            const float4 p = lds128f(sb + SM_SSUM), v = lds128f(sb + SM_SSUM + 16);
            sum = ((p.x + p.y) + (p.z + p.w)) + ((v.x + v.y) + (v.z + v.w));
        }
        uint32_t pos = 0, mine = 0;
        nrows = 0;
        {
            uint32_t c[8];
            lds128(c, sb + SM_SCNT); lds128(c + 4, sb + SM_SCNT + 16);
#pragma unroll
            for (int i = 0; i < 8; i++) {
                const uint32_t tot = __dp4a(c[i], 0x01010101u, 0u);
                nrows += tot;
                if (i < w) pos += tot;
                if (i == w) mine = c[i];
            }
        }
        const float inv = rcp_fast(sum);
        const uint32_t exc = inc - cnt;
        const uint32_t lst = sb + SM_SCO;
#pragma unroll
        for (int j = 0; j < 4; j++) {
            uint32_t a = lst + 4 * (pos + ((exc >> (8 * j)) & 0xffu));
#pragma unroll
            for (int e = 0; e < 4; e++)
                if (keep & (1u << (4 * j + e))) { sts32(a, pack_bf16(0.0f, u[j][e] * inv) | (uint32_t)(1024 * j + 4 * tid + e)); a += 4; }
            pos += (mine >> (8 * j)) & 0xffu;
        }
        if (tid < 16 && nrows + tid < ((nrows + 15) & ~15)) sts32(lst + 4 * (nrows + tid), (uint32_t)(WIN - 1));
        bar_sync<1, 256>();
    }
    if (tid == 0) TSTAMP(5);

    float o[4][4];
#pragma unroll
    for (int j = 0; j < 4; j++) { o[j][0] = o[j][1] = o[j][2] = o[j][3] = 0.f; }
    uint32_t wo_a[4][4][4];
    const int bb = lane >> 4;
    const u64* msrc = g_ll_m + (bb * 6 + 3) * 256 + 32 * w + 2 * (lane & 15);
    uint4 mc, ms;
    {
        const int nst = (nrows + 15) >> 4;
        const int nw = (nst + 7 - w) >> 3;
        const int dd = max(1, min(VD, (((nrows * VDEPTH) >> 12) + 7 - ((w * 3) & 7)) >> 3));
        u64 pol;
        asm volatile("createpolicy.fractional.L2::evict_first.b64 %0, 1.0;" : "=l"(pol));
        const char* vsrc[4];
        {
            const char* vb = reinterpret_cast<const char*>(vcache) + ((size_t)(r >> 1) * SK + (SK - WIN)) * 256 + half * 128;
            const uint32_t x0 = ((lane & 7) ^ ((lane >> 1) & 4)) << 4;
#pragma unroll
            for (int j = 0; j < 4; j++) vsrc[j] = vb + (x0 ^ (j << 4));
        }
        const uint32_t ring = sb + SM_RING + w * (VD * 2048);
        const uint32_t vdst = ring + (lane >> 3) * 512 + (lane & 7) * 16;
        const uint32_t lsrc = sb + SM_SCO + w * 64;
        auto issue = [&](int k, int sl) {
            if (k < nw) {
                uint32_t en[4];
                lds128(en, lsrc + k * 512 + (lane >> 3) * 16);
#pragma unroll
                for (int j = 0; j < 4; j++)
                    asm volatile("cp.async.cg.shared.global.L2::cache_hint [%0], [%1], 16, %2;"
                                 :: "r"(vdst + sl * 2048 + j * 128), "l"(vsrc[j] + (size_t)(en[j] & 0xffffu) * 256), "l"(pol) : "memory");
            }
            asm volatile("cp.async.commit_group;" ::: "memory");
        };
#pragma unroll 1
        for (int d = 0; d < dd; d++) issue(d, d);
        if (is_ffn) { ll_ld2(msrc, ms); ll_ld2(msrc + 256, mc); }
        {
            uint32_t* dst = g_ll_r + ((b * 16 + 2 * w) * NPP + cg) * 32 + t * 8 + g;
            tag_st(dst, 0.f, (flag & 3u) ^ 2u); tag_st(dst + NPP * 32, 0.f, (flag & 3u) ^ 2u);
        }
        const int nit = max(nw, 1), kpoll = max(nit - dd - POLL_REM, 0);
        int sl = 0;
#pragma unroll 1
        for (int k = 0; k < nit; k++) {
            if (k == kpoll) bar_arrive<4, 288>();
            uint32_t b0 = 0, b1 = 0;
            if (k < nw) {
                uint32_t e0, e1, e2, e3;
                lds64(e0, e1, lsrc + k * 512 + t * 8); lds64(e2, e3, lsrc + k * 512 + 32 + t * 8);
                b0 = __byte_perm(e0, e1, 0x7632); b1 = __byte_perm(e2, e3, 0x7632);
            }
            switch (dd) {
                case 1: asm volatile("cp.async.wait_group 0;" ::: "memory"); break;
                case 2: asm volatile("cp.async.wait_group 1;" ::: "memory"); break;
                case 3: asm volatile("cp.async.wait_group 2;" ::: "memory"); break;
                case 4: asm volatile("cp.async.wait_group 3;" ::: "memory"); break;
                case 5: asm volatile("cp.async.wait_group 4;" ::: "memory"); break;
                case 6: asm volatile("cp.async.wait_group 5;" ::: "memory"); break;
                default: asm volatile("cp.async.wait_group 6;" ::: "memory"); break;
            }
            __syncwarp();
            if (k < nw) {
                const uint32_t base = ring + sl * 2048 + tr_off;
                uint32_t a[4][4];
#pragma unroll
                for (int j = 0; j < 4; j++) ldsm4t(a[j], base ^ (j << 5));
#pragma unroll
                for (int j = 0; j < 4; j++) mma16816(o[j], a[j], b0, b1);
            }
            __syncwarp();
            issue(k + dd, sl);
            if (++sl == dd) sl = 0;
            if (k == 0) {
                mbar_wait(bar_w + 8 * (w >> 1), 1);
#pragma unroll
                for (int j = 0; j < 4; j++)
#pragma unroll
                    for (int ks = 0; ks < 4; ks++) ldsm4t(wo_a[ks][j], ((sb + SM_W + w * 8192 + tr_off) ^ (j << 5)) + ks * 2048);
                __syncwarp();
                if (lane == 0) mbar_arrive(bar_wfree2);
            }
        }
    }
    TSTAMPD(6, __float_as_uint(o[3][0]));

    const uint32_t tag = flag & 3u;
    {
        sts32f(sb + SM_RO + red_st, sel4(t, o[0][0], o[1][0], o[2][0], o[3][0]));
        sts32f(sb + SM_RO + red_st + 32, sel4(t, o[0][2], o[1][2], o[2][2], o[3][2]));
        uint32_t* dst = g_ll_r + ((b * 16 + 2 * w) * NPP + cg) * 32 + t * 8 + g;
        bar_sync<1, 256>();
        float2 v[8];
#pragma unroll
        for (int i = 0; i < 8; i++) v[i] = lds64f(sb + SM_RO + i * 256 + lane * 8);
        const float o0 = ((v[0].x + v[1].x) + (v[2].x + v[3].x)) + ((v[4].x + v[5].x) + (v[6].x + v[7].x));
        const float o1 = ((v[0].y + v[1].y) + (v[2].y + v[3].y)) + ((v[4].y + v[5].y) + (v[6].y + v[7].y));
        const uint32_t op = pack_bf16(o0, o1);
        uint32_t bf[8];
#pragma unroll
        for (int i = 0; i < 8; i++) bf[i] = __shfl_sync(0xffffffffu, op, 4 * i + t);
        float d[2][4][4];
#pragma unroll
        for (int ks = 0; ks < 4; ks++)
#pragma unroll
            for (int j = 0; j < 4; j++) {
                if (ks < 2) mma16816z(d[ks][j], wo_a[ks][j], bf[2 * ks], bf[2 * ks + 1]);
                else        mma16816(d[ks & 1][j], wo_a[ks][j], bf[2 * ks], bf[2 * ks + 1]);
            }
        const float r0 = sel4(t, d[0][0][0], d[0][0][2], d[0][1][0], d[0][1][2]) + sel4(t, d[1][0][0], d[1][0][2], d[1][1][0], d[1][1][2]);
        const float r1 = sel4(t, d[0][2][0], d[0][2][2], d[0][3][0], d[0][3][2]) + sel4(t, d[1][2][0], d[1][2][2], d[1][3][0], d[1][3][2]);
        tag_st(dst, r0, tag);
        tag_st(dst + NPP * 32, r1, tag);
        TSTAMPD(23, op);
        TSTAMPD(7, __float_as_uint(r1));
    }
    auto gather = [&](int box, int per, int n) {
        const uint32_t* src = g_ll_r + (box * NPP + per * w) * 32 + lane;
        float s0, s1;
        while (true) {
            uint32_t v[11], bad = 0;
#pragma unroll
            for (int i = 0; i < 11; i++) {
                v[i] = tag;
                if (i < 8 || i < n) asm volatile("ld.relaxed.gpu.global.u32 %0, [%1];" : "=r"(v[i]) : "l"(src + i * 32) : "memory");
            }
#pragma unroll
            for (int i = 0; i < 11; i++) {
                v[i] ^= tag; bad |= v[i];
                if (i == 0) s0 = __uint_as_float(v[i]); else if (i == 1) s1 = __uint_as_float(v[i]);
                else if (i & 1) s1 += __uint_as_float(v[i]); else s0 += __uint_as_float(v[i]);
            }
            if (__all_sync(0xffffffffu, (bad & 3u) == 0)) break;
            check_timeout(t0);
        }
        sts32f(sb + SM_RQ + w * 128 + lane * 4, s0 + s1);
        TSTAMPD(r < 32 ? 26 : 27, __float_as_uint(s0));
        bar_arrive<6, 288>();
    };
    if (!is_ffn) {
        if (r >= 96) gather(r - 96, 8, 8);
        return;
    }

    uint32_t f_a[2][4][4], w2_a[4][4];
    {
        mbar_wait(bar_f, 0);
        const uint32_t fb = sb + SM_W + l_sel * 16384 + (64 * w + l_row) * 32 + ((g & 1) << 4);
#pragma unroll
        for (int j = 0; j < 2; j++)
#pragma unroll
            for (int ks = 0; ks < 4; ks++) ldsm4t(f_a[j][ks], (fb ^ (j << 4)) + ks * 512);
        mbar_wait(bar_f2, 0);
#pragma unroll
        for (int j = 0; j < 4; j++) ldsm4t(w2_a[j], (sb + SM_W + 32768 + w * 2048 + tr_off) ^ (j << 5));
    }
    {
        while (!__all_sync(0xffffffffu, ms.y == flag && ms.w == flag && mc.y == flag && mc.w == flag)) {
            ll_ld2(msrc, ms); ll_ld2(msrc + 256, mc); check_timeout(t0);
        }
        uint32_t* dst = g_ll_r + ((32 + 4 * w) * NPP + r) * 32 + t * 8 + g;
#pragma unroll
        for (int j = 0; j < 4; j++) tag_st(dst + j * NPP * 32, 0.f, tag ^ 2u);
        uint4 xv;
        xv.y = ~flag;
        ll_poll2(g_ll_x + bb * 256 + 32 * w + 2 * (lane & 15), xv, flag, t0);
        TSTAMPD(9, xv.x);
        if (r < 32) bar_arrive<7, 288>();
        const float piv = bf_lo(__shfl_sync(0xffffffffu, xv.x, lane & 16));
        const float e0 = bf_lo(xv.x) - piv, e1 = bf_hi(xv.x) - piv, e2 = bf_lo(xv.z) - piv, e3 = bf_hi(xv.z) - piv;
        float s1 = (e0 + e1) + (e2 + e3), s2 = (e0 * e0 + e1 * e1) + (e2 * e2 + e3 * e3);
#pragma unroll
        for (int of = 1; of < 16; of <<= 1) { s1 += __shfl_xor_sync(0xffffffffu, s1, of); s2 += __shfl_xor_sync(0xffffffffu, s2, of); }
        if ((lane & 15) == 0) sts64f(sb + SM_STAT + bb * 64 + w * 8, piv + s1 * (1.0f / 64.0f), s2 - s1 * s1 * (1.0f / 64.0f));
        bar_sync<1, 256>();
        float4 st[4];
#pragma unroll
        for (int i = 0; i < 4; i++) st[i] = lds128f(sb + SM_STAT + bb * 64 + i * 16);
        const float mean = (((st[0].x + st[0].z) + (st[1].x + st[1].z)) + ((st[2].x + st[2].z) + (st[3].x + st[3].z))) * 0.125f;
        const float M2 = ((st[0].y + st[0].w) + (st[1].y + st[1].w)) + ((st[2].y + st[2].w) + (st[3].y + st[3].w));
        float dv[4];
#pragma unroll
        for (int i = 0; i < 4; i++) { const float d0 = st[i].x - mean, d1 = st[i].z - mean; dv[i] = d0 * d0 + d1 * d1; }
        const float rden = ln_rden(fmaxf(M2 * (1.0f / DM) + ((dv[0] + dv[1]) + (dv[2] + dv[3])) * 0.125f, 0.f));
        TSTAMPD(24, __float_as_uint(st[3].x));
        const uint32_t m2 = pack_bf16(mean, mean);
        const uint32_t p0 = bf2_add(bf2_mul(ln_pair(xv.x, m2, rden), mc.x), ms.x);
        const uint32_t p1 = bf2_add(bf2_mul(ln_pair(xv.z, m2, rden), mc.z), ms.z);
        TSTAMPD(25, p1);
        float d[2][4][4];
#pragma unroll
        for (int ks = 0; ks < 4; ks++) {
            const uint32_t b0 = __shfl_sync(0xffffffffu, p0, 16 * (g & 1) + 4 * ks + t);
            const uint32_t b1 = __shfl_sync(0xffffffffu, p1, 16 * (g & 1) + 4 * ks + t);
#pragma unroll
            for (int j = 0; j < 2; j++) mma16816z(d[j][ks], f_a[j][ks], b0, b1);
        }
        float acc[4];
#pragma unroll
        for (int i = 0; i < 4; i++) {
            const float u0 = (d[0][0][i] + d[0][1][i]) + (d[0][2][i] + d[0][3][i]);
            const float u1 = (d[1][0][i] + d[1][1][i]) + (d[1][2][i] + d[1][3][i]);
            acc[i] = (t & 1) ? u1 : u0;
        }
        if (t < 2) sts128f(sb + SM_RGU + w * 256 + (8 * t + g) * 16, acc[0], acc[2], acc[1], acc[3]);
        bar_sync<1, 256>();
        float2 pv[8];
#pragma unroll
        for (int i = 0; i < 8; i++) pv[i] = lds64f(sb + SM_RGU + i * 256 + (lane & 15) * 16 + bb * 8);
        const float gate = bf16r(((pv[0].x + pv[1].x) + (pv[2].x + pv[3].x)) + ((pv[4].x + pv[5].x) + (pv[6].x + pv[7].x)));
        const float up   = bf16r(((pv[0].y + pv[1].y) + (pv[2].y + pv[3].y)) + ((pv[4].y + pv[5].y) + (pv[6].y + pv[7].y)));
        TSTAMPD(10, __float_as_uint(pv[7].x));
        const float hh = bf16r(silu_f(gate)) * up;
        const int sl0 = 16 * (g & 1) + 2 * t;
        const float h0 = __shfl_sync(0xffffffffu, hh, sl0), h1 = __shfl_sync(0xffffffffu, hh, sl0 + 1);
        const float h8 = __shfl_sync(0xffffffffu, hh, sl0 + 8), h9 = __shfl_sync(0xffffffffu, hh, sl0 + 9);
        const uint32_t b0 = pack_bf16(h0, h1), b1 = pack_bf16(h8, h9);
        float f[4][4];
#pragma unroll
        for (int j = 0; j < 4; j++) mma16816z(f[j], w2_a[j], b0, b1);
#pragma unroll
        for (int j = 0; j < 4; j++) tag_st(dst + j * NPP * 32, sel4(t, f[j][0], f[j][1], f[j][2], f[j][3]), tag);
        TSTAMPD(11, __float_as_uint(f[3][3]));
        if (r < 32) {
            { const uint32_t c = clk32(); while (clk32() - c < XDELAY) ; }
            gather(32 + r, 11, w < 7 ? 11 : NFFN - 77);
        }
    }
}

typedef CUresult (*EncodeFn)(CUtensorMap*, CUtensorMapDataType, cuuint32_t, void*, const cuuint64_t*, const cuuint64_t*,
                             const cuuint32_t*, const cuuint32_t*, CUtensorMapInterleave, CUtensorMapSwizzle,
                             CUtensorMapL2promotion, CUtensorMapFloatOOBfill);

void make_map(EncodeFn enc, CUtensorMap* tm, const void* ptr, uint64_t cols, uint64_t rows, uint32_t box_cols,
              uint32_t box_rows, CUtensorMapSwizzle sw, CUtensorMapL2promotion promo) {
    cuuint64_t gd[2] = {cols, rows};
    cuuint64_t gs[1] = {cols * 2};
    cuuint32_t box[2] = {box_cols, box_rows};
    cuuint32_t es[2] = {1, 1};
    enc(tm, CU_TENSOR_MAP_DATA_TYPE_BFLOAT16, 2, const_cast<void*>(ptr), gd, gs, box, es, CU_TENSOR_MAP_INTERLEAVE_NONE,
        sw, promo, CU_TENSOR_MAP_FLOAT_OOB_FILL_NONE);
}

}

extern "C" void kernel_launch(void* const* d_in, const int* in_sizes, int n_in, void* d_out, int out_size) {
    (void)in_sizes; (void)n_in; (void)out_size;
    static EncodeFn enc = nullptr;
    if (!enc) {
        cudaDriverEntryPointQueryResult qr;
        cudaGetDriverEntryPoint("cuTensorMapEncodeTiled", (void**)&enc, cudaEnableDefault, &qr);
        cudaFuncSetAttribute(fused_decode_kernel, cudaFuncAttributeMaxDynamicSharedMemorySize, SMEM_BYTES);
    }
    Maps tm;
    const CUtensorMapSwizzle S128 = CU_TENSOR_MAP_SWIZZLE_128B;
    const CUtensorMapL2promotion P256 = CU_TENSOR_MAP_L2_PROMOTION_L2_256B, P128 = CU_TENSOR_MAP_L2_PROMOTION_L2_128B;
    make_map(enc, &tm.K, d_in[1], 128, (uint64_t)64 * SK, 64, 128, S128, P128);
    make_map(enc, &tm.V, d_in[2], 128, (uint64_t)64 * SK, 64, 128, S128, P128);
    make_map(enc, &tm.Wq, d_in[3], 4096, 512, 64, 128, S128, P256);
    make_map(enc, &tm.Wo, d_in[4], 512, 4096, 64, 64, S128, P256);
    make_map(enc, &tm.W2, d_in[8], 512, FF, 64, 16, S128, P256);
    make_map(enc, &tm.Wm, d_in[10], 6 * DM, 512, 8, 256, CU_TENSOR_MAP_SWIZZLE_NONE, P128);
    make_map(enc, &tm.Wm16, d_in[10], 6 * DM, 512, 16, 256, CU_TENSOR_MAP_SWIZZLE_32B, P128);
    make_map(enc, &tm.W1, d_in[6], FF, 512, 16, 256, CU_TENSOR_MAP_SWIZZLE_32B, P128);
    make_map(enc, &tm.W3, d_in[7], FF, 512, 16, 256, CU_TENSOR_MAP_SWIZZLE_32B, P128);
    fused_decode_kernel<<<NCTA, NTHREADS, SMEM_BYTES>>>(
        (const bf16*)d_in[0], (const bf16*)d_in[9], (const bf16*)d_in[2], (bf16*)d_out, tm);
}
```

```cpp
#include <cuda_runtime.h>
#include <cuda.h>
#include <cuda_bf16.h>
#include <stdint.h>

namespace {

typedef __nv_bfloat16 bf16;
typedef unsigned long long u64;

constexpr int DM   = 512;
constexpr int SK   = 16384;
constexpr int WIN  = 4096;
constexpr int FF   = 1376;
constexpr int NCTA = 128;
constexpr int NFFN = 86;
constexpr int NPP  = 88;
constexpr int NS   = 7;
constexpr int TILE = 16384;
#define BURST 5
#define NPF 3
#define FSTEADY 4
#define RELD 5
#define HDELAY 2400u
#define XDELAY 300u
#define J_WM 16
#define VD 7
#define VDEPTH 56
#define VT0 50000
#define VT1 2000000
#define POLL_REM 0
#define TH_MUL 1
#define THETA 4
constexpr int NTHREADS = 320;

constexpr int SM_W    = 0;
constexpr int SM_RING = 65536;
constexpr int SM_SCO  = SM_RING + NS * TILE;
constexpr int SM_SCR  = SM_SCO + 16384;
constexpr int SM_P    = SM_SCR + 16384;
constexpr int SM_RMOD = SM_P + 8192;
constexpr int SM_RQ   = SM_RMOD + 512;
constexpr int SM_RO   = SM_RQ + 2048;
constexpr int SM_RGU  = SM_RO + 2048;
constexpr int SM_SILU = SM_RGU + 2048;
constexpr int SM_STAT = SM_SILU + 2048;
constexpr int SM_SMAX = SM_STAT + 128;
constexpr int SM_SSUM = SM_SMAX + 32;
constexpr int SM_SCNT = SM_SSUM + 32;
constexpr int SM_BAR  = SM_SCNT + 40;
constexpr int SM_HIST = SM_BAR + 8 * (2 * NS + 11) + 8;
constexpr int SM_END  = SM_HIST;
static_assert(VD * 2048 * 8 <= NS * TILE, "V rings");
constexpr int SMEM_BYTES = SM_END + 1024;
static_assert(SMEM_BYTES <= 232448, "smem");

__device__ unsigned int g_epoch;
__device__ __align__(128) u64 g_ll_x[2 * 256];
__device__ __align__(128) u64 g_ll_m[2 * 6 * 256];
__device__ __align__(128) uint32_t g_ll_r[2 * 32 * NPP * 32];
#define THIST(wgt) do { } while (0)
#define TSTAMP(i) do { } while (0)
#define TSTAMPD(i, dep) do { } while (0)

__device__ __forceinline__ uint32_t smem_u32(const void* p) { return (uint32_t)__cvta_generic_to_shared(p); }
__device__ __forceinline__ uint32_t pack_bf16(float lo, float hi) {
    uint32_t r; asm("cvt.rn.bf16x2.f32 %0, %1, %2;" : "=r"(r) : "f"(hi), "f"(lo)); return r;
}
__device__ __forceinline__ float bf16r(float v) { return __uint_as_float(pack_bf16(0.0f, v)); }
__device__ __forceinline__ float bf_lo(uint32_t v) { return __uint_as_float(v << 16); }
__device__ __forceinline__ float bf_hi(uint32_t v) { return __uint_as_float(v & 0xffff0000u); }
__device__ __forceinline__ uint32_t bf2_mul(uint32_t a, uint32_t b) { uint32_t r; asm("mul.rn.bf16x2 %0, %1, %2;" : "=r"(r) : "r"(a), "r"(b)); return r; }
__device__ __forceinline__ uint32_t bf2_add(uint32_t a, uint32_t b) { uint32_t r; asm("add.rn.bf16x2 %0, %1, %2;" : "=r"(r) : "r"(a), "r"(b)); return r; }
__device__ __forceinline__ uint32_t bf2_sub(uint32_t a, uint32_t b) { uint32_t r; asm("sub.rn.bf16x2 %0, %1, %2;" : "=r"(r) : "r"(a), "r"(b)); return r; }
__device__ __forceinline__ float ex2_fast(float v) { float r; asm("ex2.approx.ftz.f32 %0, %1;" : "=f"(r) : "f"(v)); return r; }
__device__ __forceinline__ float ex2_sub(float v) { float r; asm("ex2.approx.f32 %0, %1;" : "=f"(r) : "f"(v)); return r; }
__device__ __forceinline__ float sqrt_fast(float v) { float r; asm("sqrt.approx.ftz.f32 %0, %1;" : "=f"(r) : "f"(v)); return r; }
__device__ __forceinline__ float rcp_fast(float v) { float r; asm("rcp.approx.ftz.f32 %0, %1;" : "=f"(r) : "f"(v)); return r; }
constexpr float LOG2E = 1.4426950408889634f;
__device__ __forceinline__ float silu_f(float v) { return v * rcp_fast(1.0f + ex2_fast(-LOG2E * v)); }
__device__ __forceinline__ float ln_rden(float var) { return rcp_fast(bf16r(sqrt_fast(bf16r(bf16r(var) + 1e-5f)))); }
__device__ __forceinline__ uint32_t ln_pair(uint32_t x2, uint32_t m2, float rden) {
    const uint32_t d = bf2_sub(x2, m2);
    return pack_bf16(bf_lo(d) * rden, bf_hi(d) * rden);
}

__device__ __forceinline__ void mbar_init(uint32_t bar, uint32_t cnt) {
    asm volatile("mbarrier.init.shared::cta.b64 [%0], %1;" :: "r"(bar), "r"(cnt) : "memory");
}
__device__ __forceinline__ void mbar_expect_tx(uint32_t bar, uint32_t bytes) {
    asm volatile("mbarrier.arrive.expect_tx.shared::cta.b64 _, [%0], %1;" :: "r"(bar), "r"(bytes) : "memory");
}
__device__ __forceinline__ void mbar_arrive(uint32_t bar) {
    asm volatile("mbarrier.arrive.shared::cta.b64 _, [%0];" :: "r"(bar) : "memory");
}
__device__ __forceinline__ uint32_t clk32() { uint32_t c; asm volatile("mov.u32 %0, %%clock;" : "=r"(c)); return c; }
__device__ __forceinline__ void check_timeout(uint32_t t0) { if ((int32_t)(clk32() - t0) < 0) __trap(); }
#define MBAR_WAIT_ASM(SEM) \
    asm volatile("{\n.reg .pred p;\n.reg .s32 t1;\n" \
                 "W_%=:\n" \
                 "mbarrier.try_wait.parity" SEM ".shared::cta.b64 p, [%0], %1;\n@p bra D_%=;\n" \
                 "mov.u32 t1, %%clock;\nsub.s32 t1, t1, %2;\nsetp.ge.s32 p, t1, 0;\n@p bra W_%=;\ntrap;\n" \
                 "D_%=:\n}" :: "r"(bar), "r"(parity), "r"(t0) : "memory")
__device__ __forceinline__ void mbar_wait_t(uint32_t bar, uint32_t parity, uint32_t t0) { MBAR_WAIT_ASM(""); }
__device__ __forceinline__ void mbar_wait_cluster_t(uint32_t bar, uint32_t parity, uint32_t t0) { MBAR_WAIT_ASM(".acquire.cluster"); }
#define mbar_wait(bar, parity) mbar_wait_t(bar, parity, t0)
#define mbar_wait_cluster(bar, parity) mbar_wait_cluster_t(bar, parity, t0)
__device__ __forceinline__ bool mbar_test(uint32_t bar, uint32_t parity) {
    uint32_t ok;
    asm volatile("{\n.reg .pred p;\nmbarrier.test_wait.parity.shared::cta.b64 p, [%1], %2;\nselp.u32 %0, 1, 0, p;\n}"
                 : "=r"(ok) : "r"(bar), "r"(parity) : "memory");
    return ok != 0;
}
__device__ __forceinline__ bool elect_one() {
    uint32_t p;
    asm volatile("{\n.reg .pred P;\nelect.sync _|P, 0xffffffff;\nselp.u32 %0, 1, 0, P;\n}" : "=r"(p));
    return p != 0;
}
__device__ __forceinline__ void tma2d(uint32_t dst, const CUtensorMap* tm, int c0, int c1, uint32_t bar) {
    asm volatile("cp.async.bulk.tensor.2d.shared::cluster.global.mbarrier::complete_tx::bytes [%0], [%1, {%3, %4}], [%2];"
                 :: "r"(dst), "l"(tm), "r"(bar), "r"(c0), "r"(c1) : "memory");
}
__device__ __forceinline__ void tma2d_ef(uint32_t dst, const CUtensorMap* tm, int c0, int c1, uint32_t bar, u64 pol) {
    asm volatile("cp.async.bulk.tensor.2d.shared::cluster.global.mbarrier::complete_tx::bytes.L2::cache_hint [%0], [%1, {%3, %4}], [%2], %5;"
                 :: "r"(dst), "l"(tm), "r"(bar), "r"(c0), "r"(c1), "l"(pol) : "memory");
}
__device__ __forceinline__ void ldsm2t(uint32_t& a0, uint32_t& a1, uint32_t addr) {
    asm volatile("ldmatrix.sync.aligned.m8n8.x2.trans.shared.b16 {%0,%1}, [%2];" : "=r"(a0), "=r"(a1) : "r"(addr) : "memory");
}
__device__ __forceinline__ void ldsm4(uint32_t (&a)[4], uint32_t addr) {
    asm volatile("ldmatrix.sync.aligned.m8n8.x4.shared.b16 {%0,%1,%2,%3}, [%4];"
                 : "=r"(a[0]), "=r"(a[1]), "=r"(a[2]), "=r"(a[3]) : "r"(addr) : "memory");
}
__device__ __forceinline__ void ldsm4t(uint32_t (&a)[4], uint32_t addr) {
    asm volatile("ldmatrix.sync.aligned.m8n8.x4.trans.shared.b16 {%0,%1,%2,%3}, [%4];"
                 : "=r"(a[0]), "=r"(a[1]), "=r"(a[2]), "=r"(a[3]) : "r"(addr) : "memory");
}
__device__ __forceinline__ void mma16816(float (&d)[4], const uint32_t (&a)[4], uint32_t b0, uint32_t b1) {
    asm volatile("mma.sync.aligned.m16n8k16.row.col.f32.bf16.bf16.f32 {%0,%1,%2,%3}, {%4,%5,%6,%7}, {%8,%9}, {%0,%1,%2,%3};"
                 : "+f"(d[0]), "+f"(d[1]), "+f"(d[2]), "+f"(d[3])
                 : "r"(a[0]), "r"(a[1]), "r"(a[2]), "r"(a[3]), "r"(b0), "r"(b1));
}
__device__ __forceinline__ void mma16816z(float (&d)[4], const uint32_t (&a)[4], uint32_t b0, uint32_t b1) {
    asm volatile("mma.sync.aligned.m16n8k16.row.col.f32.bf16.bf16.f32 {%0,%1,%2,%3}, {%4,%5,%6,%7}, {%8,%9}, {%10,%10,%10,%10};"
                 : "=f"(d[0]), "=f"(d[1]), "=f"(d[2]), "=f"(d[3])
                 : "r"(a[0]), "r"(a[1]), "r"(a[2]), "r"(a[3]), "r"(b0), "r"(b1), "f"(0.0f));
}
template <int ID, int N> __device__ __forceinline__ void bar_sync() { asm volatile("bar.sync %0, %1;" :: "n"(ID), "n"(N) : "memory"); }
template <int ID, int N> __device__ __forceinline__ void bar_arrive() { asm volatile("bar.arrive %0, %1;" :: "n"(ID), "n"(N) : "memory"); }
__device__ __forceinline__ void cluster_arrive_relaxed() { asm volatile("barrier.cluster.arrive.relaxed.aligned;" ::: "memory"); }
__device__ __forceinline__ void cluster_wait() { asm volatile("barrier.cluster.wait.acquire.aligned;" ::: "memory"); }

__device__ __forceinline__ void sts32f(uint32_t a, float v) { asm volatile("st.shared.f32 [%0], %1;" :: "r"(a), "f"(v) : "memory"); }
__device__ __forceinline__ void sts32(uint32_t a, uint32_t v) { asm volatile("st.shared.b32 [%0], %1;" :: "r"(a), "r"(v) : "memory"); }
__device__ __forceinline__ uint32_t lds32(uint32_t a) { uint32_t v; asm volatile("ld.shared.b32 %0, [%1];" : "=r"(v) : "r"(a) : "memory"); return v; }
__device__ __forceinline__ float2 lds64f(uint32_t a) { float2 v; asm volatile("ld.shared.v2.f32 {%0,%1}, [%2];" : "=f"(v.x), "=f"(v.y) : "r"(a) : "memory"); return v; }
__device__ __forceinline__ float4 lds128f(uint32_t a) { float4 v; asm volatile("ld.shared.v4.f32 {%0,%1,%2,%3}, [%4];" : "=f"(v.x), "=f"(v.y), "=f"(v.z), "=f"(v.w) : "r"(a) : "memory"); return v; }
__device__ __forceinline__ void lds64(uint32_t& x, uint32_t& y, uint32_t a) { asm volatile("ld.shared.v2.b32 {%0,%1}, [%2];" : "=r"(x), "=r"(y) : "r"(a) : "memory"); }
__device__ __forceinline__ void lds128(uint32_t* v, uint32_t a) { asm volatile("ld.shared.v4.b32 {%0,%1,%2,%3}, [%4];" : "=r"(v[0]), "=r"(v[1]), "=r"(v[2]), "=r"(v[3]) : "r"(a) : "memory"); }
__device__ __forceinline__ void sts64f(uint32_t a, float x, float y) { asm volatile("st.shared.v2.f32 [%0], {%1,%2};" :: "r"(a), "f"(x), "f"(y) : "memory"); }
__device__ __forceinline__ void sts64(uint32_t a, uint32_t x, uint32_t y) { asm volatile("st.shared.v2.b32 [%0], {%1,%2};" :: "r"(a), "r"(x), "r"(y) : "memory"); }
__device__ __forceinline__ void sts128(uint32_t a, uint32_t x, uint32_t y, uint32_t z, uint32_t w) { asm volatile("st.shared.v4.b32 [%0], {%1,%2,%3,%4};" :: "r"(a), "r"(x), "r"(y), "r"(z), "r"(w) : "memory"); }
__device__ __forceinline__ void sts128f(uint32_t a, float x, float y, float z, float w) { asm volatile("st.shared.v4.f32 [%0], {%1,%2,%3,%4};" :: "r"(a), "f"(x), "f"(y), "f"(z), "f"(w) : "memory"); }

__device__ __forceinline__ void ll_st(u64* p, uint32_t lo, uint32_t hi) {
    asm volatile("{\n.reg .b64 v;\nmov.b64 v, {%1, %2};\nst.relaxed.gpu.global.b64 [%0], v;\n}" :: "l"(p), "r"(lo), "r"(hi) : "memory");
}
__device__ __forceinline__ void ll_ld2(const u64* p, uint4& v) {
    asm volatile("{\n.reg .b64 a, b;\nld.relaxed.gpu.global.v2.b64 {a, b}, [%4];\nmov.b64 {%0, %1}, a;\nmov.b64 {%2, %3}, b;\n}"
                 : "=r"(v.x), "=r"(v.y), "=r"(v.z), "=r"(v.w) : "l"(p) : "memory");
}
__device__ __forceinline__ void ll_poll2(const u64* p, uint4& v, uint32_t flag, uint32_t t0) {
    while (!__all_sync(0xffffffffu, v.y == flag && v.w == flag)) { ll_ld2(p, v); check_timeout(t0); }
}
__device__ __forceinline__ void tag_st(uint32_t* p, float v, uint32_t tag) {
    asm volatile("st.relaxed.gpu.global.u32 [%0], %1;" :: "l"(p), "r"((__float_as_uint(v) & ~3u) | tag) : "memory");
}
__device__ __forceinline__ float sel4(int t, float a, float b, float c, float d) {
    float lo = (t & 1) ? b : a, hi = (t & 1) ? d : c;
    return (t & 2) ? hi : lo;
}

struct Maps { CUtensorMap K, V, Wq, Wo, W2, Wm, W1, W3, Wm16; };

__global__ void __cluster_dims__(2, 1, 1) __launch_bounds__(NTHREADS, 1)
fused_decode_kernel(const bf16* __restrict__ x, const bf16* __restrict__ cvec, const bf16* __restrict__ vcache,
                    bf16* __restrict__ out, const __grid_constant__ Maps tm)
{
    extern __shared__ uint8_t smem_raw[];
    const uint32_t sb = (smem_u32(smem_raw) + 1023u) & ~1023u;
    const int tid = threadIdx.x, lane = tid & 31;
    const int warp = __shfl_sync(0xffffffffu, tid >> 5, 0);
    const uint32_t t0 = clk32();
    const int r = blockIdx.x;
    const int half = r & 1, b = r >> 6, cg = r & 63;
    const int g = lane >> 2, t = lane & 3;
    const uint32_t bar_w = sb + SM_BAR, bar_full = bar_w + 32, bar_sc = bar_full + 8 * NS;
    const uint32_t bar_f = bar_sc + 8, bar_m = bar_f + 8, bar_wfree = bar_m + 8, bar_go = bar_wfree + 8, bar_empty = bar_go + 8;
    const uint32_t bar_f2 = bar_empty + 8 * NS, bar_wfree2 = bar_f2 + 8;
    const bool is_ffn = r < NFFN;
    const uint32_t l_row = (lane & 7) + 8 * (lane >> 4);
    const uint32_t l_sel = (lane >> 3) & 1;

    if (warp == 8) {
        const bool el = elect_one();
        const int kv_row0 = (r >> 1) * SK + (SK - WIN);
        u64 pol;
        asm volatile("createpolicy.fractional.L2::evict_first.b64 %0, 1.0;" : "=l"(pol));
        if (el) {
            TSTAMP(0);
            mbar_init(bar_m, 1);
#pragma unroll
            for (int i = 0; i < BURST; i++) mbar_init(bar_w + 8 * i, 1);
            asm volatile("fence.mbarrier_init.release.cluster;" ::: "memory");
            mbar_expect_tx(bar_m, 8192);
            tma2d(sb + SM_P, &tm.Wm, r * 8, 0, bar_m);
            tma2d(sb + SM_P + 4096, &tm.Wm, r * 8, 256, bar_m);
#pragma unroll
            for (int i = 0; i < BURST; i++) {
                mbar_expect_tx(bar_w + 8 * i, TILE);
                if (i < 4) tma2d(sb + i * TILE, &tm.Wq, cg * 64, i * 128, bar_w + 8 * i);
                else       tma2d_ef(sb + i * TILE, &tm.K, half * 64, kv_row0 + (i - 4) * 128, bar_w + 8 * i, pol);
            }
            TSTAMP(8);
#pragma unroll
            for (int i = BURST; i < 2 * NS + 11; i++) if (i != NS + 6) mbar_init(bar_w + 8 * i, (i < NS + 9 || i == 2 * NS + 9) ? 1 : 8);
            asm volatile("fence.mbarrier_init.release.cluster;" ::: "memory");
            mbar_expect_tx(bar_sc, 16384);
        }
        __syncwarp();
        cluster_arrive_relaxed();
#pragma unroll 1
        for (int u = BURST; u < 4 + NS + NPF; u++) {
            const uint32_t gb = bar_w + 8 * (u >= BURST + 2 ? u - (BURST - 2) : 2 * (u - BURST) + 1);
            bool rel;
            while (!((rel = mbar_test(bar_empty, 0)) && (u >= 4 + NS || mbar_test(bar_w + 8 * (u - RELD), 0))) && !mbar_test(gb, 0)) check_timeout(t0);
            if (u < 4 + NS) {
                if (el) {
                    mbar_expect_tx(bar_w + 8 * u, TILE);
                    tma2d_ef(sb + u * TILE, &tm.K, half * 64, kv_row0 + (u - 4) * 128, bar_w + 8 * u, pol);
                }
            } else {
                if (rel) break;
                if (el) asm volatile("cp.async.bulk.prefetch.tensor.2d.L2.global.tile [%0, {%1, %2}];"
                                     :: "l"(&tm.K), "r"(half * 64), "r"(kv_row0 + (u - 4) * 128) : "memory");
            }
        }
        if (el) TSTAMP(16);
        int slot = 0, gslot = NS - FSTEADY;
        uint32_t ph = 0, gph = 0;
#pragma unroll 1
        for (int j = NS; j < 36; j++) {
            if (j == J_WM && el) {
                mbar_expect_tx(bar_m, 16384);
                tma2d(sb + SM_W, &tm.Wm16, 2 * DM + r * 16, 0, bar_m);
                tma2d(sb + SM_W + 8192, &tm.Wm16, 2 * DM + r * 16, 256, bar_m);
            }
            if (j < 32) mbar_wait(bar_empty + 8 * slot, ph);
            else if (j == 32) mbar_wait(bar_wfree, 0);
            if (FSTEADY < NS) {
                mbar_wait(bar_full + 8 * gslot, gph);
                if (++gslot == NS) { gslot = 0; gph ^= 1u; }
            }
            if (j < 32) {
                if (el) {
                    mbar_expect_tx(bar_full + 8 * slot, TILE);
                    tma2d_ef(sb + SM_RING + slot * TILE, &tm.K, half * 64, kv_row0 + j * 128, bar_full + 8 * slot, pol);
                }
                if (++slot == NS) { slot = 0; ph ^= 1u; }
            } else if (el) {
                const int i = 2 * (j - 32);
                mbar_expect_tx(bar_w + 4 * i, TILE);
                tma2d(sb + SM_W + i * 8192, &tm.Wo, i * 64, cg * 64, bar_w + 4 * i);
                tma2d(sb + SM_W + i * 8192 + 8192, &tm.Wo, i * 64 + 64, cg * 64, bar_w + 4 * i);
            }
        }
        if (el) TSTAMP(17);
        if (is_ffn) {
            mbar_wait(bar_go, 0);
            mbar_wait(bar_wfree2, 0);
            if (el) TSTAMP(18);
            if (el) {
                mbar_expect_tx(bar_f, 32768);
#pragma unroll 1
                for (int i = 0; i < 4; i++) tma2d(sb + SM_W + i * 8192, i < 2 ? &tm.W1 : &tm.W3, r * 16, (i & 1) * 256, bar_f);
                mbar_expect_tx(bar_f2, TILE);
#pragma unroll 1
                for (int i = 0; i < 8; i++) tma2d(sb + SM_W + 32768 + i * 2048, &tm.W2, i * 64, r * 16, bar_f2);
            }
        }
        cluster_wait();
        return;
    }

    uint32_t flag;
    asm volatile("ld.relaxed.gpu.global.u32 %0, [%1];" : "=r"(flag) : "l"(&g_epoch) : "memory");

    if (warp == 9) {
        const uint4* xp = reinterpret_cast<const uint4*>(x + b * DM);
        const uint4 xa = __ldg(xp + lane), xb = __ldg(xp + 32 + lane);
        cluster_arrive_relaxed();
        flag += 1u;
        const uint32_t xw[8] = {xa.x, xa.y, xa.z, xa.w, xb.x, xb.y, xb.z, xb.w};
        float s = 0.f;
#pragma unroll
        for (int i = 0; i < 8; i++) s += bf_lo(xw[i]) + bf_hi(xw[i]);
#pragma unroll 1
        for (int o = 16; o > 0; o >>= 1) s += __shfl_xor_sync(0xffffffffu, s, o);
        const float mean = s * (1.0f / DM);
        float m2 = 0.f;
#pragma unroll
        for (int i = 0; i < 8; i++) { const float d0 = bf_lo(xw[i]) - mean, d1 = bf_hi(xw[i]) - mean; m2 += d0 * d0; m2 += d1 * d1; }
#pragma unroll 1
        for (int o = 16; o > 0; o >>= 1) m2 += __shfl_xor_sync(0xffffffffu, m2, o);
        {
            const uint32_t mm = pack_bf16(mean, mean);
            const float rden = ln_rden(m2 * (1.0f / DM));
            sts128(sb + SM_RO + lane * 16, ln_pair(xa.x, mm, rden), ln_pair(xa.y, mm, rden), ln_pair(xa.z, mm, rden), ln_pair(xa.w, mm, rden));
            sts128(sb + SM_RO + 512 + lane * 16, ln_pair(xb.x, mm, rden), ln_pair(xb.y, mm, rden), ln_pair(xb.z, mm, rden), ln_pair(xb.w, mm, rden));
        }
        const int fpos = (cg >> 1) * 8 + 2 * t + (cg & 1);
        if (lane == 0) TSTAMP(19);
        bar_sync<2, 288>();
        {
            float4 v = lds128f(sb + SM_RMOD + g * 64 + t * 16);
#pragma unroll
            for (int o = 4; o < 32; o <<= 1) {
                v.x += __shfl_xor_sync(0xffffffffu, v.x, o); v.y += __shfl_xor_sync(0xffffffffu, v.y, o);
                v.z += __shfl_xor_sync(0xffffffffu, v.z, o); v.w += __shfl_xor_sync(0xffffffffu, v.w, o);
            }
            uint32_t m = g ? pack_bf16(v.y, v.w) : pack_bf16(v.x, v.z);
            if (b) m = bf2_add(m, 0x3f803f80u);
            if (lane < 8) ll_st(&g_ll_m[(g * 6 + b) * 256 + fpos], m, flag);
        }
        if (lane == 0) TSTAMP(1);
        cluster_wait();

        {
            float d[2][4];
#pragma unroll
            for (int i = 0; i < 4; i++) { d[0][i] = d[1][i] = 0.f; }
            mbar_wait(bar_m, 1);
            const uint32_t base = sb + SM_W + l_row * 32 + ((l_sel ^ (g & 1)) << 4);
            const uint32_t sa = sb + SM_SILU + (g & 1) * 1024 + t * 4;
#pragma unroll 1
            for (int ks = 0; ks < 32; ks += 2) {
                uint32_t a0[4], a1[4];
                ldsm4t(a0, base + ks * 512);
                ldsm4t(a1, base + ks * 512 + 512);
                mma16816(d[0], a0, lds32(sa + ks * 32), lds32(sa + ks * 32 + 16));
                mma16816(d[1], a1, lds32(sa + ks * 32 + 32), lds32(sa + ks * 32 + 48));
            }
            if (lane == 0) mbar_arrive(bar_wfree);
            const uint32_t p0 = pack_bf16(d[0][0] + d[1][0], d[0][2] + d[1][2]), p1 = pack_bf16(d[0][1] + d[1][1], d[0][3] + d[1][3]);
            const uint32_t a0 = __shfl_sync(0xffffffffu, p0, 8 * t), a1 = __shfl_sync(0xffffffffu, p0, 8 * t + 4);
            const uint32_t c0 = __shfl_sync(0xffffffffu, p1, 8 * t), c1 = __shfl_sync(0xffffffffu, p1, 8 * t + 4);
            uint32_t m = __byte_perm((g & 2) ? c0 : a0, (g & 2) ? c1 : a1, (g & 1) ? 0x7632 : 0x5410);
            if ((r >> 5) == 2) m = bf2_add(m, 0x3f803f80u);
            if (lane < 16) ll_st(&g_ll_m[((g >> 1) * 6 + 2) * 256 + r * 8 + 2 * t + (g & 1)], m, flag);
            if (lane == 0) TSTAMP(13);
        }

        bar_sync<4, 288>();
        if (is_ffn) {
            const uint32_t* base = g_ll_r + ((r & 31) * NPP + lane) * 32;
            while (true) {
                uint32_t v0, v1;
                asm volatile("ld.relaxed.gpu.global.u32 %0, [%1];" : "=r"(v0) : "l"(base) : "memory");
                asm volatile("ld.relaxed.gpu.global.u32 %0, [%1];" : "=r"(v1) : "l"(base + 1024) : "memory");
                const int cnt = __popc(__ballot_sync(0xffffffffu, ((v0 ^ flag) & 3u) == 0)) + __popc(__ballot_sync(0xffffffffu, ((v1 ^ flag) & 3u) == 0));
                if (cnt >= THETA + TH_MUL * ((r >> 1) & 7)) break;
                __nanosleep(200);
                check_timeout(t0);
            }
            if (lane == 0) mbar_arrive(bar_go);
        }
        if (r >= 32 && r < 96) return;
        const bool fin = r < 32;
        const int fb = fin ? (lane >> 3) & 1 : (r >> 4) & 1;
        const int col = fin ? r * 16 + (lane >> 4) * 8 + (lane & 7) : (r & 15) * 32 + lane;
        const int wi = (col >> 4) * 8 + (col & 6) + ((col >> 3) & 1);
        u64 gw, xq;
        while (true) {
            asm volatile("ld.relaxed.gpu.global.b64 %0, [%1];" : "=l"(gw) : "l"(&g_ll_m[(fb * 6 + (fin ? 5 : 2)) * 256 + wi]) : "memory");
            if (__all_sync(0xffffffffu, (uint32_t)(gw >> 32) == flag)) break;
            check_timeout(t0);
        }
        if (fin) {
            bar_sync<7, 288>();
            while (true) {
                asm volatile("ld.relaxed.gpu.global.b64 %0, [%1];" : "=l"(xq) : "l"(&g_ll_x[fb * 256 + wi]) : "memory");
                if (__all_sync(0xffffffffu, (uint32_t)(xq >> 32) == flag)) break;
                check_timeout(t0);
            }
        } else {
            xq = __ldg(reinterpret_cast<const uint32_t*>(x + fb * DM) + (col >> 1));
        }
        const float xin = (lane & 1) ? bf_hi((uint32_t)xq) : bf_lo((uint32_t)xq);
        const float gt = (lane & 1) ? bf_hi((uint32_t)gw) : bf_lo((uint32_t)gw);
        sts32f(sb + SM_RMOD + lane * 4, xin + gt);
        bar_sync<6, 288>();
        float v[8];
#pragma unroll
        for (int i = 0; i < 8; i++) v[i] = __uint_as_float(lds32(sb + SM_RQ + i * 128 + lane * 4));
        const float res = xin + bf16r(gt * bf16r(((v[0] + v[1]) + (v[2] + v[3])) + ((v[4] + v[5]) + (v[6] + v[7]))));
        const uint32_t pr = pack_bf16(res, __shfl_down_sync(0xffffffffu, res, 1));
        if (!(lane & 1)) {
            if (fin) reinterpret_cast<uint32_t*>(out)[(fb * DM + col) >> 1] = pr;
            else ll_st(&g_ll_x[fb * 256 + wi], pr, flag);
        }
        TSTAMPD(fin ? 12 : 14, pr);
        if (r == 0 && lane == 0) asm volatile("st.relaxed.gpu.global.u32 [%0], %1;" :: "l"(&g_epoch), "r"(flag) : "memory");
        return;
    }

    const int w = warp;
    {
        const uint32_t* cp = reinterpret_cast<const uint32_t*>(cvec + 64 * w) + lane;
        const uint32_t c0 = __ldg(cp), c1 = __ldg(cp + DM / 2);
        cluster_arrive_relaxed();
        sts32(sb + SM_SILU + w * 128 + lane * 4, pack_bf16(silu_f(bf_lo(c0)), silu_f(bf_hi(c0))));
        sts32(sb + SM_SILU + 1024 + w * 128 + lane * 4, pack_bf16(silu_f(bf_lo(c1)), silu_f(bf_hi(c1))));
        cluster_wait();
        __syncwarp();
        uint32_t sc[8];
#pragma unroll
        for (int i = 0; i < 8; i++) sc[i] = lds32(sb + SM_SILU + (g & 1) * 1024 + w * 128 + i * 16 + t * 4);
        mbar_wait(bar_m, 0);
        if (tid == 0) TSTAMP(15);
        float d[2][4];
        uint32_t a[4][4];
#pragma unroll
        for (int ks = 0; ks < 4; ks++) {
            ldsm2t(a[ks][0], a[ks][2], sb + SM_P + (64 * w + 16 * ks + (lane & 15)) * 16);
            a[ks][1] = a[ks][3] = 0u;
        }
        mma16816z(d[0], a[0], sc[0], sc[1]); mma16816z(d[1], a[1], sc[2], sc[3]);
        mma16816(d[0], a[2], sc[4], sc[5]);  mma16816(d[1], a[3], sc[6], sc[7]);
        if (t == 0) sts64f(sb + SM_RMOD + w * 64 + g * 8, d[0][0] + d[1][0], d[0][1] + d[1][1]);
        bar_sync<2, 288>();
    }
    flag += 1u;

    const uint32_t tr_off = l_row * 128 + ((l_sel ^ (lane & 7)) << 4);
    const uint32_t red_st = (w * 64 + 16 * t + g) * 4;
    uint32_t qf[8];
    {
        const uint32_t lnp = sb + SM_RO + (32 * w + 8 * ((lane >> 2) & 3) + t) * 4;
        const uint32_t ln0 = lds32(lnp), ln1 = lds32(lnp + 16);
        uint4 hv; hv.y = ~flag;
        { const uint32_t c = clk32(); while (clk32() - c < HDELAY) ; }
        ll_poll2(g_ll_m + (b * 6 + (lane >> 4)) * 256 + 32 * w + 2 * (lane & 15), hv, flag, t0);
        uint32_t a[4][4][4];
        mbar_wait(bar_w + 8 * (w >> 1), 0);
        const uint32_t base = sb + SM_W + w * 8192 + tr_off;
#pragma unroll
        for (int j = 0; j < 4; j++)
#pragma unroll
            for (int ks = 0; ks < 4; ks++) ldsm4t(a[ks][j], (base ^ (j << 5)) + ks * 2048);
        if (tid == 0) TSTAMP(2);
        hv.x = bf2_add(bf2_mul(ln0, __shfl_down_sync(0xffffffffu, hv.x, 16)), hv.x);
        hv.z = bf2_add(bf2_mul(ln1, __shfl_down_sync(0xffffffffu, hv.z, 16)), hv.z);
        float d[4][4];
#pragma unroll
        for (int ks = 0; ks < 4; ks++) {
            const uint32_t b0 = __shfl_sync(0xffffffffu, hv.x, 4 * ks + t);
            const uint32_t b1 = __shfl_sync(0xffffffffu, hv.z, 4 * ks + t);
#pragma unroll
            for (int j = 0; j < 4; j++) { if (ks == 0) mma16816z(d[j], a[ks][j], b0, b1); else mma16816(d[j], a[ks][j], b0, b1); }
        }
        sts32f(sb + SM_RQ + red_st, sel4(t, d[0][0], d[1][0], d[2][0], d[3][0]));
        sts32f(sb + SM_RQ + red_st + 32, sel4(t, d[0][2], d[1][2], d[2][2], d[3][2]));
        bar_sync<1, 256>();
        float q0 = 0.f, q1 = 0.f;
#pragma unroll
        for (int i = 0; i < 8; i++) { float2 v = lds64f(sb + SM_RQ + i * 256 + lane * 8); q0 += v.x; q1 += v.y; }
        const uint32_t qp = pack_bf16(q0, q1);
#pragma unroll
        for (int i = 0; i < 8; i++) qf[i] = __shfl_sync(0xffffffffu, qp, 4 * i + t);
        if (tid == 0) TSTAMP(3);
    }

    int slot = 0;
    uint32_t ph = 0;
    {
        const uint32_t k_off = sb + SM_RING + (16 * w + (lane & 7) + 8 * l_sel) * 128 + (((lane >> 4) ^ (lane & 7)) << 4);
        uint32_t rem_sc, rem_bar;
        asm("mapa.shared::cluster.u32 %0, %1, %2;" : "=r"(rem_sc) : "r"(sb + SM_SCR), "r"(half ^ 1));
        asm("mapa.shared::cluster.u32 %0, %1, %2;" : "=r"(rem_bar) : "r"(bar_sc), "r"(half ^ 1));
        const uint32_t s_off = (16 * w + 8 * (t & 1) + g) * 4;
#pragma unroll 1
        for (int kt = 0; kt < 32; kt++) {
            mbar_wait(bar_full + 8 * slot, ph);
            if (tid == 0) THIST(8);
            const uint32_t base = k_off + slot * TILE;
            uint32_t a[4][4];
#pragma unroll
            for (int ks = 0; ks < 4; ks++) ldsm4(a[ks], base ^ (ks << 5));
            float d0[4], d1[4];
            mma16816z(d0, a[0], qf[0], qf[1]); mma16816z(d1, a[1], qf[2], qf[3]);
            mma16816(d0, a[2], qf[4], qf[5]); mma16816(d1, a[3], qf[6], qf[7]);
            if (lane == 0) mbar_arrive(bar_empty + 8 * slot);
            const float v = (t & 1) ? d0[2] + d1[2] : d0[0] + d1[0];
            if (t < 2) sts32f(sb + SM_SCO + kt * 512 + s_off, v);
            else asm volatile("st.async.weak.shared::cluster.mbarrier::complete_tx::bytes.f32 [%0], %1, [%2];"
                              :: "r"(rem_sc + kt * 512 + s_off), "f"(v), "r"(rem_bar) : "memory");
            if (++slot == NS) { slot = 0; ph ^= 1; }
        }
    }
    if (tid == 0) TSTAMP(4);
    int nrows;
    {
        bar_sync<1, 256>();
        if (tid == 0) TSTAMP(20);
        mbar_wait_cluster(bar_sc, 0);
        if (tid == 0) TSTAMP(21);
        const uint32_t sa = sb + SM_SCO + tid * 16;
        float u[4][4];
        float mx = -INFINITY;
#pragma unroll
        for (int j = 0; j < 4; j++) {
            const float4 p = lds128f(sa + j * 4096), v = lds128f(sa + j * 4096 + 16384);
            u[j][0] = bf16r(bf16r(p.x + v.x) * 0.08838834764831845f); u[j][1] = bf16r(bf16r(p.y + v.y) * 0.08838834764831845f);
            u[j][2] = bf16r(bf16r(p.z + v.z) * 0.08838834764831845f); u[j][3] = bf16r(bf16r(p.w + v.w) * 0.08838834764831845f);
            mx = fmaxf(fmaxf(mx, fmaxf(u[j][0], u[j][1])), fmaxf(u[j][2], u[j][3]));
        }
#pragma unroll
        for (int o = 16; o > 0; o >>= 1) mx = fmaxf(mx, __shfl_xor_sync(0xffffffffu, mx, o));
        if (lane == 0) sts32f(sb + SM_SMAX + w * 4, mx);
        bar_sync<1, 256>();
        {
            const float4 p = lds128f(sb + SM_SMAX), v = lds128f(sb + SM_SMAX + 16);
            mx = fmaxf(fmaxf(fmaxf(p.x, p.y), fmaxf(p.z, p.w)), fmaxf(fmaxf(v.x, v.y), fmaxf(v.z, v.w)));
        }
        if (tid == 0) TSTAMPD(22, __float_as_uint(mx));
        float sum = 0.f;
        uint32_t keep = 0, cnt = 0;
#pragma unroll
        for (int j = 0; j < 4; j++) {
#pragma unroll
            for (int e = 0; e < 4; e++) {
                const float xx = (u[j][e] - mx) * LOG2E;
                if (!(xx < -134.0625f)) { keep |= 1u << (4 * j + e); cnt += 1u << (8 * j); }
                u[j][e] = ex2_sub(xx);
            }
            sum += (u[j][0] + u[j][1]) + (u[j][2] + u[j][3]);
        }
        uint32_t inc = cnt;
#pragma unroll
        for (int o = 1; o < 32; o <<= 1) {
            const uint32_t v = __shfl_up_sync(0xffffffffu, inc, o);
            if (lane >= o) inc += v;
            sum += __shfl_xor_sync(0xffffffffu, sum, o);
        }
        if (lane == 31) { sts32f(sb + SM_SSUM + w * 4, sum); sts32(sb + SM_SCNT + w * 4, inc); }
        if (tid == 0) sts32(sb + SM_SCNT + 32, clk32() - t0);
        bar_sync<1, 256>();
        {
            const float4 p = lds128f(sb + SM_SSUM), v = lds128f(sb + SM_SSUM + 16);
            sum = ((p.x + p.y) + (p.z + p.w)) + ((v.x + v.y) + (v.z + v.w));
        }
        uint32_t pos = 0, mine = 0;
        nrows = 0;
        {
            uint32_t c[8];
            lds128(c, sb + SM_SCNT); lds128(c + 4, sb + SM_SCNT + 16);
#pragma unroll
            for (int i = 0; i < 8; i++) {
                const uint32_t tot = __dp4a(c[i], 0x01010101u, 0u);
                nrows += tot;
                if (i < w) pos += tot;
                if (i == w) mine = c[i];
            }
        }
        if (tid == 0) TSTAMPD(28, __float_as_uint(sum));
        const float inv = rcp_fast(sum);
        const uint32_t exc = inc - cnt;
        const uint32_t lst = sb + SM_SCO;
#pragma unroll
        for (int j = 0; j < 4; j++) {
            uint32_t a = lst + 4 * (pos + ((exc >> (8 * j)) & 0xffu));
#pragma unroll
            for (int e = 0; e < 4; e++)
                if (keep & (1u << (4 * j + e))) { sts32(a, pack_bf16(0.0f, u[j][e] * inv) | (uint32_t)(1024 * j + 4 * tid + e)); a += 4; }
            pos += (mine >> (8 * j)) & 0xffu;
        }
        if (tid < 16 && nrows + tid < ((nrows + 15) & ~15)) sts32(lst + 4 * (nrows + tid), (uint32_t)(WIN - 1));
        bar_sync<1, 256>();
    }
    if (tid == 0) TSTAMP(5);

    float o[4][4];
#pragma unroll
    for (int j = 0; j < 4; j++) { o[j][0] = o[j][1] = o[j][2] = o[j][3] = 0.f; }
    uint32_t wo_a[4][4][4];
    const int bb = lane >> 4;
    const u64* msrc = g_ll_m + (bb * 6 + 3) * 256 + 32 * w + 2 * (lane & 15);
    uint4 mc, ms;
    {
        const int nst = (nrows + 15) >> 4;
        const int late = min(max((int)lds32(sb + SM_SCNT + 32) - VT0, -VT1 / 4), VT1 / 4);
        const int dtot = max(1, min(8 * VD, (int)((float)(nrows * VDEPTH) * (1.0f / 4096.0f) * ((float)VT1 / (float)(VT1 - late)) + 0.5f)));
        const int dd = (dtot + 7 - w) >> 3;
        const int wrap = dtot - 8 * (dd - 1);
        u64 pol;
        asm volatile("createpolicy.fractional.L2::evict_first.b64 %0, 1.0;" : "=l"(pol));
        const char* vsrc[4];
        {
            const char* vb = reinterpret_cast<const char*>(vcache) + ((size_t)(r >> 1) * SK + (SK - WIN)) * 256 + half * 128;
            const uint32_t x0 = ((lane & 7) ^ ((lane >> 1) & 4)) << 4;
#pragma unroll
            for (int j = 0; j < 4; j++) vsrc[j] = vb + (x0 ^ (j << 4));
        }
        const uint32_t ring = sb + SM_RING + w * (VD * 2048);
        const uint32_t vdst = ring + (lane >> 3) * 512 + (lane & 7) * 16;
        const uint32_t lsrc = sb + SM_SCO;
        auto issue = [&](int st, int sl) {
            if (st < nst) {
                uint32_t en[4];
                lds128(en, lsrc + st * 64 + (lane >> 3) * 16);
#pragma unroll
                for (int j = 0; j < 4; j++)
                    asm volatile("cp.async.cg.shared.global.L2::cache_hint [%0], [%1], 16, %2;"
                                 :: "r"(vdst + sl * 2048 + j * 128), "l"(vsrc[j] + (size_t)(en[j] & 0xffffu) * 256), "l"(pol) : "memory");
            }
            asm volatile("cp.async.commit_group;" ::: "memory");
        };
#pragma unroll 1
        for (int d = 0; d < dd; d++) issue(w + 8 * d, d);
        if (is_ffn) { ll_ld2(msrc, ms); ll_ld2(msrc + 256, mc); }
        {
            uint32_t* dst = g_ll_r + ((b * 16 + 2 * w) * NPP + cg) * 32 + t * 8 + g;
            tag_st(dst, 0.f, (flag & 3u) ^ 2u); tag_st(dst + NPP * 32, 0.f, (flag & 3u) ^ 2u);
        }
        bool polled = false, first = true;
        int sl = 0, st = dd ? w : nst;
#pragma unroll 1
        do {
            const bool act = st < nst;
            if (!polled && st + (POLL_REM + 1) * dtot >= nst) { bar_arrive<4, 288>(); polled = true; }
            uint32_t b0 = 0, b1 = 0;
            if (act) {
                uint32_t e0, e1, e2, e3;
                lds64(e0, e1, lsrc + st * 64 + t * 8); lds64(e2, e3, lsrc + st * 64 + 32 + t * 8);
                b0 = __byte_perm(e0, e1, 0x7632); b1 = __byte_perm(e2, e3, 0x7632);
            }
            switch (dd) {
                case 0:
                case 1: asm volatile("cp.async.wait_group 0;" ::: "memory"); break;
                case 2: asm volatile("cp.async.wait_group 1;" ::: "memory"); break;
                case 3: asm volatile("cp.async.wait_group 2;" ::: "memory"); break;
                case 4: asm volatile("cp.async.wait_group 3;" ::: "memory"); break;
                case 5: asm volatile("cp.async.wait_group 4;" ::: "memory"); break;
                case 6: asm volatile("cp.async.wait_group 5;" ::: "memory"); break;
                default: asm volatile("cp.async.wait_group 6;" ::: "memory"); break;
            }
            __syncwarp();
            if (act && lane == 0) THIST(1);
            if (act) {
                const uint32_t base = ring + sl * 2048 + tr_off;
                uint32_t a[4][4];
#pragma unroll
                for (int j = 0; j < 4; j++) ldsm4t(a[j], base ^ (j << 5));
#pragma unroll
                for (int j = 0; j < 4; j++) mma16816(o[j], a[j], b0, b1);
            }
            __syncwarp();
            issue(st + dtot, sl);
            if (++sl == dd) { sl = 0; st += wrap; } else st += 8;
            if (first) {
                first = false;
                mbar_wait(bar_w + 8 * (w >> 1), 1);
#pragma unroll
                for (int j = 0; j < 4; j++)
#pragma unroll
                    for (int ks = 0; ks < 4; ks++) ldsm4t(wo_a[ks][j], ((sb + SM_W + w * 8192 + tr_off) ^ (j << 5)) + ks * 2048);
                __syncwarp();
                if (lane == 0) mbar_arrive(bar_wfree2);
            }
        } while (st < nst);
        if (!polled) bar_arrive<4, 288>();
    }
    TSTAMPD(6, __float_as_uint(o[3][0]));

    const uint32_t tag = flag & 3u;
    {
        sts32f(sb + SM_RO + red_st, sel4(t, o[0][0], o[1][0], o[2][0], o[3][0]));
        sts32f(sb + SM_RO + red_st + 32, sel4(t, o[0][2], o[1][2], o[2][2], o[3][2]));
        uint32_t* dst = g_ll_r + ((b * 16 + 2 * w) * NPP + cg) * 32 + t * 8 + g;
        bar_sync<1, 256>();
        float2 v[8];
#pragma unroll
        for (int i = 0; i < 8; i++) v[i] = lds64f(sb + SM_RO + i * 256 + lane * 8);
        const float o0 = ((v[0].x + v[1].x) + (v[2].x + v[3].x)) + ((v[4].x + v[5].x) + (v[6].x + v[7].x));
        const float o1 = ((v[0].y + v[1].y) + (v[2].y + v[3].y)) + ((v[4].y + v[5].y) + (v[6].y + v[7].y));
        const uint32_t op = pack_bf16(o0, o1);
        uint32_t bf[8];
#pragma unroll
        for (int i = 0; i < 8; i++) bf[i] = __shfl_sync(0xffffffffu, op, 4 * i + t);
        float d[2][4][4];
#pragma unroll
        for (int ks = 0; ks < 4; ks++)
#pragma unroll
            for (int j = 0; j < 4; j++) {
                if (ks < 2) mma16816z(d[ks][j], wo_a[ks][j], bf[2 * ks], bf[2 * ks + 1]);
                else        mma16816(d[ks & 1][j], wo_a[ks][j], bf[2 * ks], bf[2 * ks + 1]);
            }
        const float r0 = sel4(t, d[0][0][0], d[0][0][2], d[0][1][0], d[0][1][2]) + sel4(t, d[1][0][0], d[1][0][2], d[1][1][0], d[1][1][2]);
        const float r1 = sel4(t, d[0][2][0], d[0][2][2], d[0][3][0], d[0][3][2]) + sel4(t, d[1][2][0], d[1][2][2], d[1][3][0], d[1][3][2]);
        tag_st(dst, r0, tag);
        tag_st(dst + NPP * 32, r1, tag);
        TSTAMPD(23, op);
        TSTAMPD(7, __float_as_uint(r1));
    }
    auto gather = [&](int box, int per, int n) {
        const uint32_t* src = g_ll_r + (box * NPP + per * w) * 32 + lane;
        float s0, s1;
        while (true) {
            uint32_t v[11], bad = 0;
#pragma unroll
            for (int i = 0; i < 11; i++) {
                v[i] = tag;
                if (i < 8 || i < n) asm volatile("ld.relaxed.gpu.global.u32 %0, [%1];" : "=r"(v[i]) : "l"(src + i * 32) : "memory");
            }
#pragma unroll
            for (int i = 0; i < 11; i++) {
                v[i] ^= tag; bad |= v[i];
                if (i == 0) s0 = __uint_as_float(v[i]); else if (i == 1) s1 = __uint_as_float(v[i]);
                else if (i & 1) s1 += __uint_as_float(v[i]); else s0 += __uint_as_float(v[i]);
            }
            if (__all_sync(0xffffffffu, (bad & 3u) == 0)) break;
            check_timeout(t0);
        }
        sts32f(sb + SM_RQ + w * 128 + lane * 4, s0 + s1);
        TSTAMPD(r < 32 ? 26 : 27, __float_as_uint(s0));
        bar_arrive<6, 288>();
    };
#define DUMPH() do { } while (0)
    if (!is_ffn) {
        if (r >= 96) gather(r - 96, 8, 8);
        DUMPH();
        return;
    }

    uint32_t f_a[2][4][4], w2_a[4][4];
    {
        mbar_wait(bar_f, 0);
        const uint32_t fb = sb + SM_W + l_sel * 16384 + (64 * w + l_row) * 32 + ((g & 1) << 4);
#pragma unroll
        for (int j = 0; j < 2; j++)
#pragma unroll
            for (int ks = 0; ks < 4; ks++) ldsm4t(f_a[j][ks], (fb ^ (j << 4)) + ks * 512);
        mbar_wait(bar_f2, 0);
#pragma unroll
        for (int j = 0; j < 4; j++) ldsm4t(w2_a[j], (sb + SM_W + 32768 + w * 2048 + tr_off) ^ (j << 5));
    }
    {
        while (!__all_sync(0xffffffffu, ms.y == flag && ms.w == flag && mc.y == flag && mc.w == flag)) {
            ll_ld2(msrc, ms); ll_ld2(msrc + 256, mc); check_timeout(t0);
        }
        uint32_t* dst = g_ll_r + ((32 + 4 * w) * NPP + r) * 32 + t * 8 + g;
#pragma unroll
        for (int j = 0; j < 4; j++) tag_st(dst + j * NPP * 32, 0.f, tag ^ 2u);
        uint4 xv;
        xv.y = ~flag;
        ll_poll2(g_ll_x + bb * 256 + 32 * w + 2 * (lane & 15), xv, flag, t0);
        TSTAMPD(9, xv.x);
        if (r < 32) bar_arrive<7, 288>();
        const float piv = bf_lo(__shfl_sync(0xffffffffu, xv.x, lane & 16));
        const float e0 = bf_lo(xv.x) - piv, e1 = bf_hi(xv.x) - piv, e2 = bf_lo(xv.z) - piv, e3 = bf_hi(xv.z) - piv;
        float s1 = (e0 + e1) + (e2 + e3), s2 = (e0 * e0 + e1 * e1) + (e2 * e2 + e3 * e3);
#pragma unroll
        for (int of = 1; of < 16; of <<= 1) { s1 += __shfl_xor_sync(0xffffffffu, s1, of); s2 += __shfl_xor_sync(0xffffffffu, s2, of); }
        if ((lane & 15) == 0) sts64f(sb + SM_STAT + bb * 64 + w * 8, piv + s1 * (1.0f / 64.0f), s2 - s1 * s1 * (1.0f / 64.0f));
        bar_sync<1, 256>();
        float4 st[4];
#pragma unroll
        for (int i = 0; i < 4; i++) st[i] = lds128f(sb + SM_STAT + bb * 64 + i * 16);
        const float mean = (((st[0].x + st[0].z) + (st[1].x + st[1].z)) + ((st[2].x + st[2].z) + (st[3].x + st[3].z))) * 0.125f;
        const float M2 = ((st[0].y + st[0].w) + (st[1].y + st[1].w)) + ((st[2].y + st[2].w) + (st[3].y + st[3].w));
        float dv[4];
#pragma unroll
        for (int i = 0; i < 4; i++) { const float d0 = st[i].x - mean, d1 = st[i].z - mean; dv[i] = d0 * d0 + d1 * d1; }
        const float rden = ln_rden(fmaxf(M2 * (1.0f / DM) + ((dv[0] + dv[1]) + (dv[2] + dv[3])) * 0.125f, 0.f));
        TSTAMPD(24, __float_as_uint(st[3].x));
        const uint32_t m2 = pack_bf16(mean, mean);
        const uint32_t p0 = bf2_add(bf2_mul(ln_pair(xv.x, m2, rden), mc.x), ms.x);
        const uint32_t p1 = bf2_add(bf2_mul(ln_pair(xv.z, m2, rden), mc.z), ms.z);
        TSTAMPD(25, p1);
        float d[2][4][4];
#pragma unroll
        for (int ks = 0; ks < 4; ks++) {
            const uint32_t b0 = __shfl_sync(0xffffffffu, p0, 16 * (g & 1) + 4 * ks + t);
            const uint32_t b1 = __shfl_sync(0xffffffffu, p1, 16 * (g & 1) + 4 * ks + t);
#pragma unroll
            for (int j = 0; j < 2; j++) mma16816z(d[j][ks], f_a[j][ks], b0, b1);
        }
        float acc[4];
#pragma unroll
        for (int i = 0; i < 4; i++) {
            const float u0 = (d[0][0][i] + d[0][1][i]) + (d[0][2][i] + d[0][3][i]);
            const float u1 = (d[1][0][i] + d[1][1][i]) + (d[1][2][i] + d[1][3][i]);
            acc[i] = (t & 1) ? u1 : u0;
        }
        if (t < 2) sts128f(sb + SM_RGU + w * 256 + (8 * t + g) * 16, acc[0], acc[2], acc[1], acc[3]);
        bar_sync<1, 256>();
        float2 pv[8];
#pragma unroll
        for (int i = 0; i < 8; i++) pv[i] = lds64f(sb + SM_RGU + i * 256 + (lane & 15) * 16 + bb * 8);
        const float gate = bf16r(((pv[0].x + pv[1].x) + (pv[2].x + pv[3].x)) + ((pv[4].x + pv[5].x) + (pv[6].x + pv[7].x)));
        const float up   = bf16r(((pv[0].y + pv[1].y) + (pv[2].y + pv[3].y)) + ((pv[4].y + pv[5].y) + (pv[6].y + pv[7].y)));
        TSTAMPD(10, __float_as_uint(pv[7].x));
        const float hh = bf16r(silu_f(gate)) * up;
        const int sl0 = 16 * (g & 1) + 2 * t;
        const float h0 = __shfl_sync(0xffffffffu, hh, sl0), h1 = __shfl_sync(0xffffffffu, hh, sl0 + 1);
        const float h8 = __shfl_sync(0xffffffffu, hh, sl0 + 8), h9 = __shfl_sync(0xffffffffu, hh, sl0 + 9);
        const uint32_t b0 = pack_bf16(h0, h1), b1 = pack_bf16(h8, h9);
        float f[4][4];
#pragma unroll
        for (int j = 0; j < 4; j++) mma16816z(f[j], w2_a[j], b0, b1);
#pragma unroll
        for (int j = 0; j < 4; j++) tag_st(dst + j * NPP * 32, sel4(t, f[j][0], f[j][1], f[j][2], f[j][3]), tag);
        TSTAMPD(11, __float_as_uint(f[3][3]));
        if (r < 32) {
            { const uint32_t c = clk32(); while (clk32() - c < XDELAY) ; }
            gather(32 + r, 11, w < 7 ? 11 : NFFN - 77);
        }
        DUMPH();
    }
}

typedef CUresult (*EncodeFn)(CUtensorMap*, CUtensorMapDataType, cuuint32_t, void*, const cuuint64_t*, const cuuint64_t*,
                             const cuuint32_t*, const cuuint32_t*, CUtensorMapInterleave, CUtensorMapSwizzle,
                             CUtensorMapL2promotion, CUtensorMapFloatOOBfill);

void make_map(EncodeFn enc, CUtensorMap* tm, const void* ptr, uint64_t cols, uint64_t rows, uint32_t box_cols,
              uint32_t box_rows, CUtensorMapSwizzle sw, CUtensorMapL2promotion promo) {
    cuuint64_t gd[2] = {cols, rows};
    cuuint64_t gs[1] = {cols * 2};
    cuuint32_t box[2] = {box_cols, box_rows};
    cuuint32_t es[2] = {1, 1};
    enc(tm, CU_TENSOR_MAP_DATA_TYPE_BFLOAT16, 2, const_cast<void*>(ptr), gd, gs, box, es, CU_TENSOR_MAP_INTERLEAVE_NONE,
        sw, promo, CU_TENSOR_MAP_FLOAT_OOB_FILL_NONE);
}

}

extern "C" void kernel_launch(void* const* d_in, const int* in_sizes, int n_in, void* d_out, int out_size) {
    (void)in_sizes; (void)n_in; (void)out_size;
    static EncodeFn enc = nullptr;
    if (!enc) {
        cudaDriverEntryPointQueryResult qr;
        cudaGetDriverEntryPoint("cuTensorMapEncodeTiled", (void**)&enc, cudaEnableDefault, &qr);
        cudaFuncSetAttribute(fused_decode_kernel, cudaFuncAttributeMaxDynamicSharedMemorySize, SMEM_BYTES);
    }
    Maps tm;
    const CUtensorMapSwizzle S128 = CU_TENSOR_MAP_SWIZZLE_128B;
    const CUtensorMapL2promotion P256 = CU_TENSOR_MAP_L2_PROMOTION_L2_256B, P128 = CU_TENSOR_MAP_L2_PROMOTION_L2_128B;
    make_map(enc, &tm.K, d_in[1], 128, (uint64_t)64 * SK, 64, 128, S128, P128);
    make_map(enc, &tm.V, d_in[2], 128, (uint64_t)64 * SK, 64, 128, S128, P128);
    make_map(enc, &tm.Wq, d_in[3], 4096, 512, 64, 128, S128, P256);
    make_map(enc, &tm.Wo, d_in[4], 512, 4096, 64, 64, S128, P256);
    make_map(enc, &tm.W2, d_in[8], 512, FF, 64, 16, S128, P256);
    make_map(enc, &tm.Wm, d_in[10], 6 * DM, 512, 8, 256, CU_TENSOR_MAP_SWIZZLE_NONE, P128);
    make_map(enc, &tm.Wm16, d_in[10], 6 * DM, 512, 16, 256, CU_TENSOR_MAP_SWIZZLE_32B, P128);
    make_map(enc, &tm.W1, d_in[6], FF, 512, 16, 256, CU_TENSOR_MAP_SWIZZLE_32B, P128);
    make_map(enc, &tm.W3, d_in[7], FF, 512, 16, 256, CU_TENSOR_MAP_SWIZZLE_32B, P128);
    fused_decode_kernel<<<NCTA, NTHREADS, SMEM_BYTES>>>(
        (const bf16*)d_in[0], (const bf16*)d_in[9], (const bf16*)d_in[2], (bf16*)d_out, tm);
}
```

```cpp
#include <cuda_runtime.h>
#include <cuda.h>
#include <cuda_bf16.h>
#include <stdint.h>

namespace {

typedef __nv_bfloat16 bf16;
typedef unsigned long long u64;

constexpr int DM   = 512;
constexpr int SK   = 16384;
constexpr int WIN  = 4096;
constexpr int FF   = 1376;
constexpr int NCTA = 128;
constexpr int NFFN = 86;
constexpr int NPP  = 88;
constexpr int NS   = 7;
constexpr int TILE = 16384;
#define BURST 5
#define NPF 3
#define FSTEADY 4
#define RELD 5
#define HDELAY 2400u
#define XDELAY 300u
#define PF_J 35
#define PF_J2 32
#define PF_MASK 0
#define VD 7
#define VDEPTH 50
#define KLAG 2
#define VT0 38000
#define VT1 1e9f
#define VKAPPA 0.0f
#define VBOOST 0
#define POLL_REM 0
#define TH_MUL 1
#define THETA 4
constexpr int NTHREADS = 320;

constexpr int SM_W    = 0;
constexpr int SM_RING = 65536;
constexpr int SM_SCO  = SM_RING + NS * TILE;
constexpr int SM_SCR  = SM_SCO + 16384;
constexpr int SM_P    = SM_SCR + 16384;
constexpr int SM_RMOD = SM_P + 8192;
constexpr int SM_RQ   = SM_RMOD + 512;
constexpr int SM_RO   = SM_RQ + 2048;
constexpr int SM_RGU  = SM_RO + 2048;
constexpr int SM_SILU = SM_RGU + 2048;
constexpr int SM_STAT = SM_SILU + 2048;
constexpr int SM_SMAX = SM_STAT + 128;
constexpr int SM_SSUM = SM_SMAX + 32;
constexpr int SM_SCNT = SM_SSUM + 32;
constexpr int SM_BAR  = SM_SCNT + 40;
constexpr int SM_HIST = SM_BAR + 8 * (2 * NS + 14);
constexpr int SM_END  = SM_HIST;
static_assert(VD * 2048 * 8 <= NS * TILE, "V rings");
constexpr int SMEM_BYTES = SM_END + 1024;
static_assert(SMEM_BYTES <= 232448, "smem");

__device__ unsigned int g_epoch;
__device__ __align__(128) u64 g_ll_x[2 * 256];
__device__ __align__(128) u64 g_ll_m[2 * 6 * 256];
__device__ __align__(128) uint32_t g_ll_r[2 * 32 * NPP * 32];
#define THIST(wgt) do { } while (0)
#define TSTAMP(i) do { } while (0)
#define TSTAMPD(i, dep) do { } while (0)

__device__ __forceinline__ uint32_t smem_u32(const void* p) { return (uint32_t)__cvta_generic_to_shared(p); }
__device__ __forceinline__ uint32_t pack_bf16(float lo, float hi) {
    uint32_t r; asm("cvt.rn.bf16x2.f32 %0, %1, %2;" : "=r"(r) : "f"(hi), "f"(lo)); return r;
}
__device__ __forceinline__ float bf16r(float v) { return __uint_as_float(pack_bf16(0.0f, v)); }
__device__ __forceinline__ float bf_lo(uint32_t v) { return __uint_as_float(v << 16); }
__device__ __forceinline__ float bf_hi(uint32_t v) { return __uint_as_float(v & 0xffff0000u); }
__device__ __forceinline__ uint32_t bf2_mul(uint32_t a, uint32_t b) { uint32_t r; asm("mul.rn.bf16x2 %0, %1, %2;" : "=r"(r) : "r"(a), "r"(b)); return r; }
__device__ __forceinline__ uint32_t bf2_add(uint32_t a, uint32_t b) { uint32_t r; asm("add.rn.bf16x2 %0, %1, %2;" : "=r"(r) : "r"(a), "r"(b)); return r; }
__device__ __forceinline__ uint32_t bf2_sub(uint32_t a, uint32_t b) { uint32_t r; asm("sub.rn.bf16x2 %0, %1, %2;" : "=r"(r) : "r"(a), "r"(b)); return r; }
__device__ __forceinline__ float ex2_fast(float v) { float r; asm("ex2.approx.ftz.f32 %0, %1;" : "=f"(r) : "f"(v)); return r; }
__device__ __forceinline__ float ex2_sub(float v) { float r; asm("ex2.approx.f32 %0, %1;" : "=f"(r) : "f"(v)); return r; }
__device__ __forceinline__ float sqrt_fast(float v) { float r; asm("sqrt.approx.ftz.f32 %0, %1;" : "=f"(r) : "f"(v)); return r; }
__device__ __forceinline__ float rcp_fast(float v) { float r; asm("rcp.approx.ftz.f32 %0, %1;" : "=f"(r) : "f"(v)); return r; }
constexpr float LOG2E = 1.4426950408889634f;
__device__ __forceinline__ float silu_f(float v) { return v * rcp_fast(1.0f + ex2_fast(-LOG2E * v)); }
__device__ __forceinline__ float score_round(float v) { return bf16r(bf16r(v) * 0.08838834764831845f); }
__device__ __forceinline__ float warp_max(float v) {
    int i = __float_as_int(v);
    i ^= (i >> 31) & 0x7fffffff;
    i = __reduce_max_sync(0xffffffffu, i);
    i ^= (i >> 31) & 0x7fffffff;
    return __int_as_float(i);
}
__device__ __forceinline__ float ln_rden(float var) { return rcp_fast(bf16r(sqrt_fast(bf16r(bf16r(var) + 1e-5f)))); }
__device__ __forceinline__ uint32_t ln_pair(uint32_t x2, uint32_t m2, float rden) {
    const uint32_t d = bf2_sub(x2, m2);
    return pack_bf16(bf_lo(d) * rden, bf_hi(d) * rden);
}

__device__ __forceinline__ void mbar_init(uint32_t bar, uint32_t cnt) {
    asm volatile("mbarrier.init.shared::cta.b64 [%0], %1;" :: "r"(bar), "r"(cnt) : "memory");
}
__device__ __forceinline__ void mbar_expect_tx(uint32_t bar, uint32_t bytes) {
    asm volatile("mbarrier.arrive.expect_tx.shared::cta.b64 _, [%0], %1;" :: "r"(bar), "r"(bytes) : "memory");
}
__device__ __forceinline__ void mbar_arrive(uint32_t bar) {
    asm volatile("mbarrier.arrive.shared::cta.b64 _, [%0];" :: "r"(bar) : "memory");
}
__device__ __forceinline__ uint32_t clk32() { uint32_t c; asm volatile("mov.u32 %0, %%clock;" : "=r"(c)); return c; }
__device__ __forceinline__ void check_timeout(uint32_t t0) { if ((int32_t)(clk32() - t0) < 0) __trap(); }
#define MBAR_WAIT_ASM(SEM) \
    asm volatile("{\n.reg .pred p;\n.reg .s32 t1;\n" \
                 "W_%=:\n" \
                 "mbarrier.try_wait.parity" SEM ".shared::cta.b64 p, [%0], %1;\n@p bra D_%=;\n" \
                 "mov.u32 t1, %%clock;\nsub.s32 t1, t1, %2;\nsetp.ge.s32 p, t1, 0;\n@p bra W_%=;\ntrap;\n" \
                 "D_%=:\n}" :: "r"(bar), "r"(parity), "r"(t0) : "memory")
__device__ __forceinline__ void mbar_wait_t(uint32_t bar, uint32_t parity, uint32_t t0) { MBAR_WAIT_ASM(""); }
__device__ __forceinline__ void mbar_wait_cluster_t(uint32_t bar, uint32_t parity, uint32_t t0) { MBAR_WAIT_ASM(".acquire.cluster"); }
#define mbar_wait(bar, parity) mbar_wait_t(bar, parity, t0)
#define mbar_wait_cluster(bar, parity) mbar_wait_cluster_t(bar, parity, t0)
__device__ __forceinline__ bool mbar_test(uint32_t bar, uint32_t parity) {
    uint32_t ok;
    asm volatile("{\n.reg .pred p;\nmbarrier.test_wait.parity.shared::cta.b64 p, [%1], %2;\nselp.u32 %0, 1, 0, p;\n}"
                 : "=r"(ok) : "r"(bar), "r"(parity) : "memory");
    return ok != 0;
}
__device__ __forceinline__ bool elect_one() {
    uint32_t p;
    asm volatile("{\n.reg .pred P;\nelect.sync _|P, 0xffffffff;\nselp.u32 %0, 1, 0, P;\n}" : "=r"(p));
    return p != 0;
}
__device__ __forceinline__ void tma2d(uint32_t dst, const CUtensorMap* tm, int c0, int c1, uint32_t bar) {
    asm volatile("cp.async.bulk.tensor.2d.shared::cluster.global.mbarrier::complete_tx::bytes [%0], [%1, {%3, %4}], [%2];"
                 :: "r"(dst), "l"(tm), "r"(bar), "r"(c0), "r"(c1) : "memory");
}
__device__ __forceinline__ void tma_pf(const CUtensorMap* tm, int c0, int c1) {
    asm volatile("cp.async.bulk.prefetch.tensor.2d.L2.global.tile [%0, {%1, %2}];" :: "l"(tm), "r"(c0), "r"(c1) : "memory");
}
__device__ __forceinline__ void bulk_pf(const void* p, uint32_t bytes) {
    asm volatile("cp.async.bulk.prefetch.L2.global [%0], %1;" :: "l"(p), "r"(bytes) : "memory");
}
__device__ __forceinline__ void tma2d_ef(uint32_t dst, const CUtensorMap* tm, int c0, int c1, uint32_t bar, u64 pol) {
    asm volatile("cp.async.bulk.tensor.2d.shared::cluster.global.mbarrier::complete_tx::bytes.L2::cache_hint [%0], [%1, {%3, %4}], [%2], %5;"
                 :: "r"(dst), "l"(tm), "r"(bar), "r"(c0), "r"(c1), "l"(pol) : "memory");
}
__device__ __forceinline__ void ldsm2t(uint32_t& a0, uint32_t& a1, uint32_t addr) {
    asm volatile("ldmatrix.sync.aligned.m8n8.x2.trans.shared.b16 {%0,%1}, [%2];" : "=r"(a0), "=r"(a1) : "r"(addr) : "memory");
}
__device__ __forceinline__ void ldsm4(uint32_t (&a)[4], uint32_t addr) {
    asm volatile("ldmatrix.sync.aligned.m8n8.x4.shared.b16 {%0,%1,%2,%3}, [%4];"
                 : "=r"(a[0]), "=r"(a[1]), "=r"(a[2]), "=r"(a[3]) : "r"(addr) : "memory");
}
__device__ __forceinline__ void ldsm4t(uint32_t (&a)[4], uint32_t addr) {
    asm volatile("ldmatrix.sync.aligned.m8n8.x4.trans.shared.b16 {%0,%1,%2,%3}, [%4];"
                 : "=r"(a[0]), "=r"(a[1]), "=r"(a[2]), "=r"(a[3]) : "r"(addr) : "memory");
}
__device__ __forceinline__ void mma16816(float (&d)[4], const uint32_t (&a)[4], uint32_t b0, uint32_t b1) {
    asm volatile("mma.sync.aligned.m16n8k16.row.col.f32.bf16.bf16.f32 {%0,%1,%2,%3}, {%4,%5,%6,%7}, {%8,%9}, {%0,%1,%2,%3};"
                 : "+f"(d[0]), "+f"(d[1]), "+f"(d[2]), "+f"(d[3])
                 : "r"(a[0]), "r"(a[1]), "r"(a[2]), "r"(a[3]), "r"(b0), "r"(b1));
}
__device__ __forceinline__ void mma16816z(float (&d)[4], const uint32_t (&a)[4], uint32_t b0, uint32_t b1) {
    asm volatile("mma.sync.aligned.m16n8k16.row.col.f32.bf16.bf16.f32 {%0,%1,%2,%3}, {%4,%5,%6,%7}, {%8,%9}, {%10,%10,%10,%10};"
                 : "=f"(d[0]), "=f"(d[1]), "=f"(d[2]), "=f"(d[3])
                 : "r"(a[0]), "r"(a[1]), "r"(a[2]), "r"(a[3]), "r"(b0), "r"(b1), "f"(0.0f));
}
template <int ID, int N> __device__ __forceinline__ void bar_sync() { asm volatile("bar.sync %0, %1;" :: "n"(ID), "n"(N) : "memory"); }
template <int ID, int N> __device__ __forceinline__ void bar_arrive() { asm volatile("bar.arrive %0, %1;" :: "n"(ID), "n"(N) : "memory"); }
__device__ __forceinline__ void cluster_arrive_relaxed() { asm volatile("barrier.cluster.arrive.relaxed.aligned;" ::: "memory"); }
__device__ __forceinline__ void cluster_wait() { asm volatile("barrier.cluster.wait.acquire.aligned;" ::: "memory"); }

__device__ __forceinline__ void sts32f(uint32_t a, float v) { asm volatile("st.shared.f32 [%0], %1;" :: "r"(a), "f"(v) : "memory"); }
__device__ __forceinline__ void sts32(uint32_t a, uint32_t v) { asm volatile("st.shared.b32 [%0], %1;" :: "r"(a), "r"(v) : "memory"); }
__device__ __forceinline__ uint32_t lds32(uint32_t a) { uint32_t v; asm volatile("ld.shared.b32 %0, [%1];" : "=r"(v) : "r"(a) : "memory"); return v; }
__device__ __forceinline__ float2 lds64f(uint32_t a) { float2 v; asm volatile("ld.shared.v2.f32 {%0,%1}, [%2];" : "=f"(v.x), "=f"(v.y) : "r"(a) : "memory"); return v; }
__device__ __forceinline__ float4 lds128f(uint32_t a) { float4 v; asm volatile("ld.shared.v4.f32 {%0,%1,%2,%3}, [%4];" : "=f"(v.x), "=f"(v.y), "=f"(v.z), "=f"(v.w) : "r"(a) : "memory"); return v; }
__device__ __forceinline__ void lds64(uint32_t& x, uint32_t& y, uint32_t a) { asm volatile("ld.shared.v2.b32 {%0,%1}, [%2];" : "=r"(x), "=r"(y) : "r"(a) : "memory"); }
__device__ __forceinline__ void lds128(uint32_t* v, uint32_t a) { asm volatile("ld.shared.v4.b32 {%0,%1,%2,%3}, [%4];" : "=r"(v[0]), "=r"(v[1]), "=r"(v[2]), "=r"(v[3]) : "r"(a) : "memory"); }
__device__ __forceinline__ void sts64f(uint32_t a, float x, float y) { asm volatile("st.shared.v2.f32 [%0], {%1,%2};" :: "r"(a), "f"(x), "f"(y) : "memory"); }
__device__ __forceinline__ void sts64(uint32_t a, uint32_t x, uint32_t y) { asm volatile("st.shared.v2.b32 [%0], {%1,%2};" :: "r"(a), "r"(x), "r"(y) : "memory"); }
__device__ __forceinline__ void sts128(uint32_t a, uint32_t x, uint32_t y, uint32_t z, uint32_t w) { asm volatile("st.shared.v4.b32 [%0], {%1,%2,%3,%4};" :: "r"(a), "r"(x), "r"(y), "r"(z), "r"(w) : "memory"); }
__device__ __forceinline__ void sts128f(uint32_t a, float x, float y, float z, float w) { asm volatile("st.shared.v4.f32 [%0], {%1,%2,%3,%4};" :: "r"(a), "f"(x), "f"(y), "f"(z), "f"(w) : "memory"); }

__device__ __forceinline__ void ll_st(u64* p, uint32_t lo, uint32_t hi) {
    asm volatile("{\n.reg .b64 v;\nmov.b64 v, {%1, %2};\nst.relaxed.gpu.global.b64 [%0], v;\n}" :: "l"(p), "r"(lo), "r"(hi) : "memory");
}
__device__ __forceinline__ void ll_ld2(const u64* p, uint4& v) {
    asm volatile("{\n.reg .b64 a, b;\nld.relaxed.gpu.global.v2.b64 {a, b}, [%4];\nmov.b64 {%0, %1}, a;\nmov.b64 {%2, %3}, b;\n}"
                 : "=r"(v.x), "=r"(v.y), "=r"(v.z), "=r"(v.w) : "l"(p) : "memory");
}
__device__ __forceinline__ void ll_poll2(const u64* p, uint4& v, uint32_t flag, uint32_t t0) {
    while (!__all_sync(0xffffffffu, v.y == flag && v.w == flag)) { ll_ld2(p, v); check_timeout(t0); }
}
__device__ __forceinline__ void tag_st(uint32_t* p, float v, uint32_t tag) {
    asm volatile("st.relaxed.gpu.global.u32 [%0], %1;" :: "l"(p), "r"((__float_as_uint(v) & ~3u) | tag) : "memory");
}
__device__ __forceinline__ float sel4(int t, float a, float b, float c, float d) {
    float lo = (t & 1) ? b : a, hi = (t & 1) ? d : c;
    return (t & 2) ? hi : lo;
}

struct Maps { CUtensorMap K, V, Wq, Wo, W2, Wm, W1, W3, Wm16; };

__global__ void __cluster_dims__(2, 1, 1) __launch_bounds__(NTHREADS, 1)
fused_decode_kernel(const bf16* __restrict__ x, const bf16* __restrict__ cvec, const bf16* __restrict__ vcache,
                    const bf16* __restrict__ wmod, const bf16* __restrict__ w1p, const bf16* __restrict__ w3p, const bf16* __restrict__ w2p,
                    bf16* __restrict__ out, const __grid_constant__ Maps tm)
{
    extern __shared__ uint8_t smem_raw[];
    const uint32_t sb = (smem_u32(smem_raw) + 1023u) & ~1023u;
    const int tid = threadIdx.x, lane = tid & 31;
    const int warp = __shfl_sync(0xffffffffu, tid >> 5, 0);
    const uint32_t t0 = clk32();
    const int r = blockIdx.x;
    const int half = r & 1, b = r >> 6, cg = r & 63;
    const int g = lane >> 2, t = lane & 3;
    const uint32_t bar_w = sb + SM_BAR, bar_full = bar_w + 32;
    const uint32_t bar_f = bar_full + 8 * NS + 8, bar_m = bar_f + 8, bar_wfree = bar_m + 8, bar_go = bar_wfree + 8, bar_empty = bar_go + 8;
    const uint32_t bar_f2 = bar_empty + 8 * NS, bar_sc = bar_f2 + 8;
    const bool is_ffn = r < NFFN;
    const uint32_t l_row = (lane & 7) + 8 * (lane >> 4);
    const uint32_t l_sel = (lane >> 3) & 1;

    if (warp == 8) {
        const bool el = elect_one();
        const int kv_row0 = (r >> 1) * SK + (SK - WIN);
        u64 pol;
        asm volatile("createpolicy.fractional.L2::evict_first.b64 %0, 1.0;" : "=l"(pol));
        if (el) {
            TSTAMP(0);
            mbar_init(bar_m, 1);
#pragma unroll
            for (int i = 0; i < BURST; i++) mbar_init(bar_w + 8 * i, 1);
            asm volatile("fence.mbarrier_init.release.cluster;" ::: "memory");
            mbar_expect_tx(bar_m, 8192);
            tma2d(sb + SM_P, &tm.Wm, r * 8, 0, bar_m);
            tma2d(sb + SM_P + 4096, &tm.Wm, r * 8, 256, bar_m);
#pragma unroll
            for (int i = 0; i < BURST; i++) {
                mbar_expect_tx(bar_w + 8 * i, TILE);
                if (i < 4) tma2d(sb + i * TILE, &tm.Wq, cg * 64, i * 128, bar_w + 8 * i);
                else       tma2d_ef(sb + i * TILE, &tm.K, half * 64, kv_row0 + (i - 4) * 128, bar_w + 8 * i, pol);
            }
            TSTAMP(8);
#pragma unroll
            for (int i = BURST; i < 2 * NS + 14; i++) if (i != NS + 6) mbar_init(bar_w + 8 * i, ((i < NS + 9 && i != NS + 7) || i >= 2 * NS + 9) ? 1 : 8);
            asm volatile("fence.mbarrier_init.release.cluster;" ::: "memory");
#pragma unroll
            for (int i = 0; i < 4; i++) mbar_expect_tx(bar_sc + 8 * i, 4096);
        }
        __syncwarp();
        cluster_arrive_relaxed();
#pragma unroll 1
        for (int u = BURST; u < 4 + NS + NPF; u++) {
            const uint32_t gb = bar_w + 8 * (u >= BURST + 2 ? u - (BURST - 2) : 2 * (u - BURST) + 1);
            bool rel;
            while (!((rel = mbar_test(bar_empty, 0)) && (u >= 4 + NS || mbar_test(bar_w + 8 * (u - RELD), 0))) && !mbar_test(gb, 0)) check_timeout(t0);
            if (u < 4 + NS) {
                if (el) {
                    mbar_expect_tx(bar_w + 8 * u, TILE);
                    tma2d_ef(sb + u * TILE, &tm.K, half * 64, kv_row0 + (u - 4) * 128, bar_w + 8 * u, pol);
                }
            } else {
                if (rel) break;
                if (el) asm volatile("cp.async.bulk.prefetch.tensor.2d.L2.global.tile [%0, {%1, %2}];"
                                     :: "l"(&tm.K), "r"(half * 64), "r"(kv_row0 + (u - 4) * 128) : "memory");
            }
        }
        if (el) TSTAMP(16);
        int slot = 0, gslot = NS - FSTEADY;
        uint32_t ph = 0, gph = 0;
#pragma unroll 1
        for (int j = NS; j < 36; j++) {
            if (j == PF_J && el) {
#pragma unroll
                for (int i = 0; i < 4; i++) bulk_pf(reinterpret_cast<const char*>(wmod) + (size_t)(4 * r + i) * (6 * DM * 2) + 2 * DM * 2, 4 * DM * 2);
            }
            if (j == PF_J2 && el) {
                if (PF_MASK & 2) bulk_pf(reinterpret_cast<const char*>(w1p) + r * (FF * DM * 2 / NCTA), FF * DM * 2 / NCTA);
                if (PF_MASK & 4) bulk_pf(reinterpret_cast<const char*>(w3p) + r * (FF * DM * 2 / NCTA), FF * DM * 2 / NCTA);
                if (PF_MASK & 8) bulk_pf(reinterpret_cast<const char*>(w2p) + r * (FF * DM * 2 / NCTA), FF * DM * 2 / NCTA);
            }
            if (j < 32) mbar_wait(bar_empty + 8 * slot, ph);
            if (FSTEADY < NS) {
                mbar_wait(bar_full + 8 * gslot, gph);
                if (++gslot == NS) { gslot = 0; gph ^= 1u; }
            }
            if (j < 32) {
                if (el) {
                    mbar_expect_tx(bar_full + 8 * slot, TILE);
                    tma2d_ef(sb + SM_RING + slot * TILE, &tm.K, half * 64, kv_row0 + j * 128, bar_full + 8 * slot, pol);
                }
                if (++slot == NS) { slot = 0; ph ^= 1u; }
            } else if (el) {
                const int i = 2 * (j - 32);
                mbar_expect_tx(bar_w + 4 * i, TILE);
                tma2d(sb + SM_W + i * 8192, &tm.Wo, i * 64, cg * 64, bar_w + 4 * i);
                tma2d(sb + SM_W + i * 8192 + 8192, &tm.Wo, i * 64 + 64, cg * 64, bar_w + 4 * i);
            }
        }
        if (el) TSTAMP(17);
        mbar_wait(bar_wfree, 0);
        if (el) {
            mbar_expect_tx(bar_m, 16384);
            tma2d(sb + SM_W + 49152, &tm.Wm16, 2 * DM + r * 16, 0, bar_m);
            tma2d(sb + SM_W + 49152 + 8192, &tm.Wm16, 2 * DM + r * 16, 256, bar_m);
        }
        if (is_ffn) {
            mbar_wait(bar_go, 0);
            if (el) TSTAMP(18);
            if (el) {
                mbar_expect_tx(bar_f, 32768);
#pragma unroll 1
                for (int i = 0; i < 4; i++) tma2d(sb + SM_W + i * 8192, i < 2 ? &tm.W1 : &tm.W3, r * 16, (i & 1) * 256, bar_f);
                mbar_expect_tx(bar_f2, TILE);
#pragma unroll 1
                for (int i = 0; i < 8; i++) tma2d(sb + SM_W + 32768 + i * 2048, &tm.W2, i * 64, r * 16, bar_f2);
            }
        }
        cluster_wait();
        return;
    }

    uint32_t flag;
    asm volatile("ld.relaxed.gpu.global.u32 %0, [%1];" : "=r"(flag) : "l"(&g_epoch) : "memory");

    if (warp == 9) {
        const uint4* xp = reinterpret_cast<const uint4*>(x + b * DM);
        const uint4 xa = __ldg(xp + lane), xb = __ldg(xp + 32 + lane);
        cluster_arrive_relaxed();
        flag += 1u;
        const uint32_t xw[8] = {xa.x, xa.y, xa.z, xa.w, xb.x, xb.y, xb.z, xb.w};
        float s = 0.f;
#pragma unroll
        for (int i = 0; i < 8; i++) s += bf_lo(xw[i]) + bf_hi(xw[i]);
#pragma unroll 1
        for (int o = 16; o > 0; o >>= 1) s += __shfl_xor_sync(0xffffffffu, s, o);
        const float mean = s * (1.0f / DM);
        float m2 = 0.f;
#pragma unroll
        for (int i = 0; i < 8; i++) { const float d0 = bf_lo(xw[i]) - mean, d1 = bf_hi(xw[i]) - mean; m2 += d0 * d0; m2 += d1 * d1; }
#pragma unroll 1
        for (int o = 16; o > 0; o >>= 1) m2 += __shfl_xor_sync(0xffffffffu, m2, o);
        {
            const uint32_t mm = pack_bf16(mean, mean);
            const float rden = ln_rden(m2 * (1.0f / DM));
            sts128(sb + SM_RO + lane * 16, ln_pair(xa.x, mm, rden), ln_pair(xa.y, mm, rden), ln_pair(xa.z, mm, rden), ln_pair(xa.w, mm, rden));
            sts128(sb + SM_RO + 512 + lane * 16, ln_pair(xb.x, mm, rden), ln_pair(xb.y, mm, rden), ln_pair(xb.z, mm, rden), ln_pair(xb.w, mm, rden));
        }
        const int fpos = (cg >> 1) * 8 + 2 * t + (cg & 1);
        if (lane == 0) TSTAMP(19);
        bar_sync<2, 288>();
        {
            float4 v = lds128f(sb + SM_RMOD + g * 64 + t * 16);
#pragma unroll
            for (int o = 4; o < 32; o <<= 1) {
                v.x += __shfl_xor_sync(0xffffffffu, v.x, o); v.y += __shfl_xor_sync(0xffffffffu, v.y, o);
                v.z += __shfl_xor_sync(0xffffffffu, v.z, o); v.w += __shfl_xor_sync(0xffffffffu, v.w, o);
            }
            uint32_t m = g ? pack_bf16(v.y, v.w) : pack_bf16(v.x, v.z);
            if (b) m = bf2_add(m, 0x3f803f80u);
            if (lane < 8) ll_st(&g_ll_m[(g * 6 + b) * 256 + fpos], m, flag);
        }
        if (lane == 0) TSTAMP(1);
        cluster_wait();

        {
            float d[2][4];
#pragma unroll
            for (int i = 0; i < 4; i++) { d[0][i] = d[1][i] = 0.f; }
            mbar_wait(bar_m, 1);
            const uint32_t base = sb + SM_W + 49152 + l_row * 32 + ((l_sel ^ (g & 1)) << 4);
            const uint32_t sa = sb + SM_SILU + (g & 1) * 1024 + t * 4;
#pragma unroll 1
            for (int ks = 0; ks < 32; ks += 2) {
                uint32_t a0[4], a1[4];
                ldsm4t(a0, base + ks * 512);
                ldsm4t(a1, base + ks * 512 + 512);
                mma16816(d[0], a0, lds32(sa + ks * 32), lds32(sa + ks * 32 + 16));
                mma16816(d[1], a1, lds32(sa + ks * 32 + 32), lds32(sa + ks * 32 + 48));
            }
            const uint32_t p0 = pack_bf16(d[0][0] + d[1][0], d[0][2] + d[1][2]), p1 = pack_bf16(d[0][1] + d[1][1], d[0][3] + d[1][3]);
            const uint32_t a0 = __shfl_sync(0xffffffffu, p0, 8 * t), a1 = __shfl_sync(0xffffffffu, p0, 8 * t + 4);
            const uint32_t c0 = __shfl_sync(0xffffffffu, p1, 8 * t), c1 = __shfl_sync(0xffffffffu, p1, 8 * t + 4);
            uint32_t m = __byte_perm((g & 2) ? c0 : a0, (g & 2) ? c1 : a1, (g & 1) ? 0x7632 : 0x5410);
            if ((r >> 5) == 2) m = bf2_add(m, 0x3f803f80u);
            if (lane < 16) ll_st(&g_ll_m[((g >> 1) * 6 + 2) * 256 + r * 8 + 2 * t + (g & 1)], m, flag);
            if (lane == 0) TSTAMP(13);
        }

        bar_sync<4, 288>();
        if (is_ffn) {
            const uint32_t* base = g_ll_r + ((r & 31) * NPP + lane) * 32;
            while (true) {
                uint32_t v0, v1;
                asm volatile("ld.relaxed.gpu.global.u32 %0, [%1];" : "=r"(v0) : "l"(base) : "memory");
                asm volatile("ld.relaxed.gpu.global.u32 %0, [%1];" : "=r"(v1) : "l"(base + 1024) : "memory");
                const int cnt = __popc(__ballot_sync(0xffffffffu, ((v0 ^ flag) & 3u) == 0)) + __popc(__ballot_sync(0xffffffffu, ((v1 ^ flag) & 3u) == 0));
                if (cnt >= THETA + TH_MUL * ((r >> 1) & 7)) break;
                __nanosleep(200);
                check_timeout(t0);
            }
            if (lane == 0) mbar_arrive(bar_go);
        }
        if (r >= 32 && r < 96) return;
        const bool fin = r < 32;
        const int fb = fin ? (lane >> 3) & 1 : (r >> 4) & 1;
        const int col = fin ? r * 16 + (lane >> 4) * 8 + (lane & 7) : (r & 15) * 32 + lane;
        const int wi = (col >> 4) * 8 + (col & 6) + ((col >> 3) & 1);
        u64 gw, xq;
        while (true) {
            asm volatile("ld.relaxed.gpu.global.b64 %0, [%1];" : "=l"(gw) : "l"(&g_ll_m[(fb * 6 + (fin ? 5 : 2)) * 256 + wi]) : "memory");
            if (__all_sync(0xffffffffu, (uint32_t)(gw >> 32) == flag)) break;
            check_timeout(t0);
        }
        if (fin) {
            bar_sync<7, 288>();
            while (true) {
                asm volatile("ld.relaxed.gpu.global.b64 %0, [%1];" : "=l"(xq) : "l"(&g_ll_x[fb * 256 + wi]) : "memory");
                if (__all_sync(0xffffffffu, (uint32_t)(xq >> 32) == flag)) break;
                check_timeout(t0);
            }
        } else {
            xq = __ldg(reinterpret_cast<const uint32_t*>(x + fb * DM) + (col >> 1));
        }
        const float xin = (lane & 1) ? bf_hi((uint32_t)xq) : bf_lo((uint32_t)xq);
        const float gt = (lane & 1) ? bf_hi((uint32_t)gw) : bf_lo((uint32_t)gw);
        sts32f(sb + SM_RMOD + lane * 4, xin + gt);
        bar_sync<6, 288>();
        float v[8];
#pragma unroll
        for (int i = 0; i < 8; i++) v[i] = __uint_as_float(lds32(sb + SM_RQ + i * 128 + lane * 4));
        const float res = xin + bf16r(gt * bf16r(((v[0] + v[1]) + (v[2] + v[3])) + ((v[4] + v[5]) + (v[6] + v[7]))));
        const uint32_t pr = pack_bf16(res, __shfl_down_sync(0xffffffffu, res, 1));
        if (!(lane & 1)) {
            if (fin) reinterpret_cast<uint32_t*>(out)[(fb * DM + col) >> 1] = pr;
            else ll_st(&g_ll_x[fb * 256 + wi], pr, flag);
        }
        TSTAMPD(fin ? 12 : 14, pr);
        if (r == 0 && lane == 0) asm volatile("st.relaxed.gpu.global.u32 [%0], %1;" :: "l"(&g_epoch), "r"(flag) : "memory");
        return;
    }

    const int w = warp;
    {
        const uint32_t* cp = reinterpret_cast<const uint32_t*>(cvec + 64 * w) + lane;
        const uint32_t c0 = __ldg(cp), c1 = __ldg(cp + DM / 2);
        cluster_arrive_relaxed();
        sts32(sb + SM_SILU + w * 128 + lane * 4, pack_bf16(silu_f(bf_lo(c0)), silu_f(bf_hi(c0))));
        sts32(sb + SM_SILU + 1024 + w * 128 + lane * 4, pack_bf16(silu_f(bf_lo(c1)), silu_f(bf_hi(c1))));
        cluster_wait();
        __syncwarp();
        uint32_t sc[8];
#pragma unroll
        for (int i = 0; i < 8; i++) sc[i] = lds32(sb + SM_SILU + (g & 1) * 1024 + w * 128 + i * 16 + t * 4);
        mbar_wait(bar_m, 0);
        if (tid == 0) TSTAMP(15);
        float d[2][4];
        uint32_t a[4][4];
#pragma unroll
        for (int ks = 0; ks < 4; ks++) {
            ldsm2t(a[ks][0], a[ks][2], sb + SM_P + (64 * w + 16 * ks + (lane & 15)) * 16);
            a[ks][1] = a[ks][3] = 0u;
        }
        mma16816z(d[0], a[0], sc[0], sc[1]); mma16816z(d[1], a[1], sc[2], sc[3]);
        mma16816(d[0], a[2], sc[4], sc[5]);  mma16816(d[1], a[3], sc[6], sc[7]);
        if (t == 0) sts64f(sb + SM_RMOD + w * 64 + g * 8, d[0][0] + d[1][0], d[0][1] + d[1][1]);
        bar_sync<2, 288>();
    }
    flag += 1u;

    const uint32_t tr_off = l_row * 128 + ((l_sel ^ (lane & 7)) << 4);
    const uint32_t red_st = (w * 64 + 16 * t + g) * 4;
    uint32_t qf[8];
    {
        const uint32_t lnp = sb + SM_RO + (32 * w + 8 * ((lane >> 2) & 3) + t) * 4;
        const uint32_t ln0 = lds32(lnp), ln1 = lds32(lnp + 16);
        uint4 hv; hv.y = ~flag;
        { const uint32_t c = clk32(); while (clk32() - c < HDELAY) ; }
        ll_poll2(g_ll_m + (b * 6 + (lane >> 4)) * 256 + 32 * w + 2 * (lane & 15), hv, flag, t0);
        uint32_t a[4][4][4];
        mbar_wait(bar_w + 8 * (w >> 1), 0);
        const uint32_t base = sb + SM_W + w * 8192 + tr_off;
#pragma unroll
        for (int j = 0; j < 4; j++)
#pragma unroll
            for (int ks = 0; ks < 4; ks++) ldsm4t(a[ks][j], (base ^ (j << 5)) + ks * 2048);
        if (tid == 0) TSTAMP(2);
        hv.x = bf2_add(bf2_mul(ln0, __shfl_down_sync(0xffffffffu, hv.x, 16)), hv.x);
        hv.z = bf2_add(bf2_mul(ln1, __shfl_down_sync(0xffffffffu, hv.z, 16)), hv.z);
        float d[4][4];
#pragma unroll
        for (int ks = 0; ks < 4; ks++) {
            const uint32_t b0 = __shfl_sync(0xffffffffu, hv.x, 4 * ks + t);
            const uint32_t b1 = __shfl_sync(0xffffffffu, hv.z, 4 * ks + t);
#pragma unroll
            for (int j = 0; j < 4; j++) { if (ks == 0) mma16816z(d[j], a[ks][j], b0, b1); else mma16816(d[j], a[ks][j], b0, b1); }
        }
        sts32f(sb + SM_RQ + red_st, sel4(t, d[0][0], d[1][0], d[2][0], d[3][0]));
        sts32f(sb + SM_RQ + red_st + 32, sel4(t, d[0][2], d[1][2], d[2][2], d[3][2]));
        bar_sync<1, 256>();
        float q0 = 0.f, q1 = 0.f;
#pragma unroll
        for (int i = 0; i < 8; i++) { float2 v = lds64f(sb + SM_RQ + i * 256 + lane * 8); q0 += v.x; q1 += v.y; }
        const uint32_t qp = pack_bf16(q0, q1);
#pragma unroll
        for (int i = 0; i < 8; i++) qf[i] = __shfl_sync(0xffffffffu, qp, 4 * i + t);
        if (tid == 0) TSTAMP(3);
    }

    int slot = 0;
    uint32_t ph = 0;
    const float ZERO_P = -92.93f;
    const uint32_t lst = sb + SM_SCO;
    float m_a = 0.f, sum_a = 0.f;
    int nst_a = 0;
    {
        const uint32_t k_off = sb + SM_RING + (16 * w + (lane & 7) + 8 * l_sel) * 128 + (((lane >> 4) ^ (lane & 7)) << 4);
        uint32_t rem_sc, rem_bar;
        asm("mapa.shared::cluster.u32 %0, %1, %2;" : "=r"(rem_sc) : "r"(sb + SM_SCR), "r"(half ^ 1));
        asm("mapa.shared::cluster.u32 %0, %1, %2;" : "=r"(rem_bar) : "r"(bar_sc), "r"(half ^ 1));
        const uint32_t s_off = (16 * w + 8 * (t & 1) + g) * 4;
        float u[3][4];
#pragma unroll
        for (int j = 0; j < 4; j++) {
#pragma unroll 1
            for (int kt = (j ? 8 * j + KLAG : 0); kt < (j < 3 ? 8 * j + 8 + KLAG : 32); kt++) {
                mbar_wait(bar_full + 8 * slot, ph);
                if (tid == 0) THIST(8);
                const uint32_t base = k_off + slot * TILE;
                uint32_t a[4][4];
#pragma unroll
                for (int ks = 0; ks < 4; ks++) ldsm4(a[ks], base ^ (ks << 5));
                float d0[4], d1[4];
                mma16816z(d0, a[0], qf[0], qf[1]); mma16816z(d1, a[1], qf[2], qf[3]);
                mma16816(d0, a[2], qf[4], qf[5]); mma16816(d1, a[3], qf[6], qf[7]);
                if (lane == 0) mbar_arrive(bar_empty + 8 * slot);
                const float v = (t & 1) ? d0[2] + d1[2] : d0[0] + d1[0];
                if (t < 2) sts32f(sb + SM_SCO + kt * 512 + s_off, v);
                else asm volatile("st.async.weak.shared::cluster.mbarrier::complete_tx::bytes.f32 [%0], %1, [%2];"
                                  :: "r"(rem_sc + kt * 512 + s_off), "f"(v), "r"(rem_bar + (kt >> 3) * 8) : "memory");
                if (++slot == NS) { slot = 0; ph ^= 1; }
            }
            if (j < 3) {
                bar_sync<1, 256>();
                mbar_wait_cluster(bar_sc + 8 * j, 0);
                const float4 p = lds128f(lst + tid * 16 + j * 4096), v = lds128f(lst + tid * 16 + j * 4096 + 16384);
                u[j][0] = score_round(p.x + v.x); u[j][1] = score_round(p.y + v.y);
                u[j][2] = score_round(p.z + v.z); u[j][3] = score_round(p.w + v.w);
            }
            if (j == 2) {
                float mx = -3.0e38f;
#pragma unroll
                for (int i = 0; i < 3; i++) mx = fmaxf(fmaxf(mx, fmaxf(u[i][0], u[i][1])), fmaxf(u[i][2], u[i][3]));
                mx = warp_max(mx);
                if (lane == 0) sts32f(sb + SM_SMAX + w * 4, mx);
                bar_sync<1, 256>();
                {
                    const float4 p = lds128f(sb + SM_SMAX), v = lds128f(sb + SM_SMAX + 16);
                    m_a = fmaxf(fmaxf(fmaxf(p.x, p.y), fmaxf(p.z, p.w)), fmaxf(fmaxf(v.x, v.y), fmaxf(v.z, v.w)));
                }
                uint32_t keep = 0, cnt = 0;
#pragma unroll
                for (int i = 0; i < 3; i++)
#pragma unroll
                    for (int e = 0; e < 4; e++) {
                        const float dlt = u[i][e] - m_a;
                        if (!(dlt < ZERO_P)) { keep |= 1u << (4 * i + e); cnt += 1u << (8 * i); }
                        u[i][e] = ex2_sub(dlt * LOG2E);
                        sum_a += u[i][e];
                    }
                uint32_t inc = cnt;
#pragma unroll
                for (int o = 1; o < 32; o <<= 1) {
                    const uint32_t v = __shfl_up_sync(0xffffffffu, inc, o);
                    if (lane >= o) inc += v;
                }
                if (lane == 31) sts32(sb + SM_SCNT + w * 4, inc);
                if (tid == 0) sts32(sb + SM_SCNT + 32, clk32() - t0);
                bar_sync<1, 256>();
                uint32_t lo = 0, hi = 0, tlo = 0, thi = 0;
                {
                    uint32_t c[8];
                    lds128(c, sb + SM_SCNT); lds128(c + 4, sb + SM_SCNT + 16);
#pragma unroll
                    for (int i = 0; i < 8; i++) {
                        const uint32_t cl = c[i] & 0x00ff00ffu, ch = (c[i] >> 8) & 0xffu;
                        tlo += cl; thi += ch;
                        if (i < w) { lo += cl; hi += ch; }
                    }
                }
                const uint32_t exc = inc - cnt;
                const uint32_t n0 = tlo & 0xffffu, n_a = n0 + thi + (tlo >> 16);
#pragma unroll
                for (int i = 0; i < 3; i++) {
                    const uint32_t pos = i == 0 ? (lo & 0xffffu) : i == 1 ? n0 + hi : n0 + thi + (lo >> 16);
                    uint32_t a = lst + 4 * (pos + ((exc >> (8 * i)) & 0xffu));
#pragma unroll
                    for (int e = 0; e < 4; e++)
                        if (keep & (1u << (4 * i + e))) { sts32f(a, u[i][e]); sts32(a + 16384, (uint32_t)(1024 * i + 4 * tid + e) * 256u); a += 4; }
                }
                nst_a = (int)(n_a + 15) >> 4;
                if (tid < 16 && n_a + tid < 16u * nst_a) { sts32(lst + 4 * (n_a + tid), 0u); sts32(lst + 16384 + 4 * (n_a + tid), (WIN - 1) * 256u); }
            }
        }
    }
    if (tid == 0) TSTAMP(4);

    float o[4][4];
#pragma unroll
    for (int j = 0; j < 4; j++) { o[j][0] = o[j][1] = o[j][2] = o[j][3] = 0.f; }
    uint32_t wo_a[4][4][4];
    const int bb = lane >> 4;
    const u64* msrc = g_ll_m + (bb * 6 + 3) * 256 + 32 * w + 2 * (lane & 15);
    uint4 mc, ms;
    {
        const float rows_est = (float)nst_a * (16.0f * 4.0f / 3.0f);
        const float late = fminf(fmaxf((float)((int)lds32(sb + SM_SCNT + 32) - VT0) * (1.0f / VT1), -0.3f), 0.3f);
        const int dtot = max(1, min(min(8 * VD, nst_a), (int)(rows_est * ((float)VDEPTH / 4096.0f) * (1.0f + VKAPPA * (rows_est * (1.0f / 2048.0f) - 1.0f)) * (1.0f + late) + 0.5f)));
        const int dd = (dtot + 7 - w) >> 3;
        const int wrap = dtot - 8 * (dd - 1);
        u64 pol;
        asm volatile("createpolicy.fractional.L2::evict_first.b64 %0, 1.0;" : "=l"(pol));
        const char* vsrc[4];
        {
            const char* vb = reinterpret_cast<const char*>(vcache) + ((size_t)(r >> 1) * SK + (SK - WIN)) * 256 + half * 128;
            const uint32_t x0 = ((lane & 7) ^ ((lane >> 1) & 4)) << 4;
#pragma unroll
            for (int j = 0; j < 4; j++) vsrc[j] = vb + (x0 ^ (j << 4));
        }
        const uint32_t ring = sb + SM_RING + w * (VD * 2048);
        const uint32_t vdst = ring + (lane >> 3) * 512 + (lane & 7) * 16;
        int ik = 0, ist = w, id = 0, isl = 0;
        float sc_a = 1.0f, sc_b = 1.0f;
        auto issue = [&]() {
            uint32_t en[4];
            lds128(en, lst + 16384 + ist * 64 + (lane >> 3) * 16);
            const float4 ev = lds128f(lst + ist * 64 + (lane >> 3) * 16);
            const float f = ist < nst_a ? sc_a : sc_b;
            const float evf[4] = {ev.x * f, ev.y * f, ev.z * f, ev.w * f};
#pragma unroll
            for (int j = 0; j < 4; j++)
                asm volatile("cp.async.cg.shared.global.L2::cache_hint [%0], [%1], 16, %2, %3;"
                             :: "r"(vdst + isl * 2048 + j * 128), "l"(vsrc[j] + en[j]), "r"(evf[j] <= 0x1p-134f ? 0 : 16), "l"(pol) : "memory");
            asm volatile("cp.async.commit_group;" ::: "memory");
            ik++;
            if (++id == dd) { id = 0; ist += wrap; } else ist += 8;
            if (++isl == VD) isl = 0;
        };
        bar_sync<1, 256>();
#pragma unroll 1
        while (ik < dd) issue();
        if (tid == 0) TSTAMP(20);
        int nst;
        {
            mbar_wait_cluster(bar_sc + 24, 0);
            if (tid == 0) TSTAMP(21);
            const float4 p = lds128f(lst + tid * 16 + 12288), v = lds128f(lst + tid * 16 + 12288 + 16384);
            float u[4] = {score_round(p.x + v.x), score_round(p.y + v.y), score_round(p.z + v.z), score_round(p.w + v.w)};
            float mx = warp_max(fmaxf(fmaxf(u[0], u[1]), fmaxf(u[2], u[3])));
            if (lane == 0) sts32f(sb + SM_SMAX + w * 4, mx);
            bar_sync<1, 256>();
            {
                const float4 p2 = lds128f(sb + SM_SMAX), v2 = lds128f(sb + SM_SMAX + 16);
                mx = fmaxf(m_a, fmaxf(fmaxf(fmaxf(p2.x, p2.y), fmaxf(p2.z, p2.w)), fmaxf(fmaxf(v2.x, v2.y), fmaxf(v2.z, v2.w))));
            }
            if (tid == 0) TSTAMPD(22, __float_as_uint(mx));
            const float ca = ex2_sub((m_a - mx) * LOG2E);
            float sum = sum_a * ca;
            uint32_t keep = 0, cnt = 0;
#pragma unroll
            for (int e = 0; e < 4; e++) {
                const float dlt = u[e] - mx;
                if (!(dlt < ZERO_P)) { keep |= 1u << e; cnt++; }
                u[e] = ex2_sub(dlt * LOG2E);
                sum += u[e];
            }
            uint32_t inc = cnt;
#pragma unroll
            for (int of = 1; of < 32; of <<= 1) {
                const uint32_t vv = __shfl_up_sync(0xffffffffu, inc, of);
                if (lane >= of) inc += vv;
                sum += __shfl_xor_sync(0xffffffffu, sum, of);
            }
            if (lane == 31) { sts32f(sb + SM_SSUM + w * 4, sum); sts32(sb + SM_SCNT + w * 4, inc); }
            bar_sync<1, 256>();
            {
                const float4 p2 = lds128f(sb + SM_SSUM), v2 = lds128f(sb + SM_SSUM + 16);
                sum = ((p2.x + p2.y) + (p2.z + p2.w)) + ((v2.x + v2.y) + (v2.z + v2.w));
            }
            if (tid == 0) TSTAMPD(28, __float_as_uint(sum));
            uint32_t pos = 16 * nst_a, n = pos;
            {
                uint32_t c[8];
                lds128(c, sb + SM_SCNT); lds128(c + 4, sb + SM_SCNT + 16);
#pragma unroll
                for (int i = 0; i < 8; i++) { n += c[i]; if (i < w) pos += c[i]; }
            }
            uint32_t a = lst + 4 * (pos + inc - cnt);
#pragma unroll
            for (int e = 0; e < 4; e++)
                if (keep & (1u << e)) { sts32f(a, u[e]); sts32(a + 16384, (uint32_t)(3072 + 4 * tid + e) * 256u); a += 4; }
            nst = (int)(n + 15) >> 4;
            if (tid < 16 && n + tid < 16u * nst) { sts32(lst + 4 * (n + tid), 0u); sts32(lst + 16384 + 4 * (n + tid), (WIN - 1) * 256u); }
            sc_b = rcp_fast(sum);
            sc_a = ca * sc_b;
            bar_sync<1, 256>();
        }
        if (tid == 0) TSTAMP(5);
        const int rounds = nst / dtot;
        const int nw = rounds * dd + max(0, (nst - rounds * dtot + 7 - w) >> 3);
        {
            uint32_t* dst = g_ll_r + ((b * 16 + 2 * w) * NPP + cg) * 32 + t * 8 + g;
            tag_st(dst, 0.f, (flag & 3u) ^ 2u); tag_st(dst + NPP * 32, 0.f, (flag & 3u) ^ 2u);
        }
        bool polled = false;
        int ck = 0, cst = w, cd = 0, csl = 0;
#pragma unroll 1
        do {
            if (!polled && ik + POLL_REM >= nw) {
                polled = true;
                bar_arrive<4, 288>();
                if (is_ffn) { ll_ld2(msrc, ms); ll_ld2(msrc + 256, mc); }
            }
            if (ck < nw) {
                const float2 e0 = lds64f(lst + cst * 64 + t * 8), e1 = lds64f(lst + cst * 64 + 32 + t * 8);
                const float sc = cst < nst_a ? sc_a : sc_b;
                const uint32_t b0 = pack_bf16(e0.x * sc, e0.y * sc), b1 = pack_bf16(e1.x * sc, e1.y * sc);
                switch (ik - ck) {
                    case 1: asm volatile("cp.async.wait_group 0;" ::: "memory"); break;
                    case 2: asm volatile("cp.async.wait_group 1;" ::: "memory"); break;
                    case 3: asm volatile("cp.async.wait_group 2;" ::: "memory"); break;
                    case 4: asm volatile("cp.async.wait_group 3;" ::: "memory"); break;
                    case 5: asm volatile("cp.async.wait_group 4;" ::: "memory"); break;
                    case 6: asm volatile("cp.async.wait_group 5;" ::: "memory"); break;
                    default: asm volatile("cp.async.wait_group 6;" ::: "memory"); break;
                }
                __syncwarp();
                if (lane == 0) THIST(1);
                const uint32_t base = ring + csl * 2048 + tr_off;
                uint32_t a[4][4];
#pragma unroll
                for (int j = 0; j < 4; j++) ldsm4t(a[j], base ^ (j << 5));
#pragma unroll
                for (int j = 0; j < 4; j++) mma16816(o[j], a[j], b0, b1);
                __syncwarp();
                if (++cd == dd) { cd = 0; cst += wrap; } else cst += 8;
                if (++csl == VD) csl = 0;
                const int cap = (nw - ik <= VBOOST) ? VD : dd;
#pragma unroll 1
                while (ik < nw && ik - (ck + 1) < cap) issue();
            }
            if (ck == 0) {
                mbar_wait(bar_w + 8 * (w >> 1), 1);
#pragma unroll
                for (int j = 0; j < 4; j++)
#pragma unroll
                    for (int ks = 0; ks < 4; ks++) ldsm4t(wo_a[ks][j], ((sb + SM_W + w * 8192 + tr_off) ^ (j << 5)) + ks * 2048);
                __syncwarp();
                if (lane == 0) mbar_arrive(bar_wfree);
            }
        } while (++ck < nw);
    }
    TSTAMPD(6, __float_as_uint(o[3][0]));

    const uint32_t tag = flag & 3u;
    {
        sts32f(sb + SM_RO + red_st, sel4(t, o[0][0], o[1][0], o[2][0], o[3][0]));
        sts32f(sb + SM_RO + red_st + 32, sel4(t, o[0][2], o[1][2], o[2][2], o[3][2]));
        uint32_t* dst = g_ll_r + ((b * 16 + 2 * w) * NPP + cg) * 32 + t * 8 + g;
        bar_sync<1, 256>();
        float2 v[8];
#pragma unroll
        for (int i = 0; i < 8; i++) v[i] = lds64f(sb + SM_RO + i * 256 + lane * 8);
        const float o0 = ((v[0].x + v[1].x) + (v[2].x + v[3].x)) + ((v[4].x + v[5].x) + (v[6].x + v[7].x));
        const float o1 = ((v[0].y + v[1].y) + (v[2].y + v[3].y)) + ((v[4].y + v[5].y) + (v[6].y + v[7].y));
        const uint32_t op = pack_bf16(o0, o1);
        uint32_t bf[8];
#pragma unroll
        for (int i = 0; i < 8; i++) bf[i] = __shfl_sync(0xffffffffu, op, 4 * i + t);
        float d[2][4][4];
#pragma unroll
        for (int ks = 0; ks < 4; ks++)
#pragma unroll
            for (int j = 0; j < 4; j++) {
                if (ks < 2) mma16816z(d[ks][j], wo_a[ks][j], bf[2 * ks], bf[2 * ks + 1]);
                else        mma16816(d[ks & 1][j], wo_a[ks][j], bf[2 * ks], bf[2 * ks + 1]);
            }
        const float r0 = sel4(t, d[0][0][0], d[0][0][2], d[0][1][0], d[0][1][2]) + sel4(t, d[1][0][0], d[1][0][2], d[1][1][0], d[1][1][2]);
        const float r1 = sel4(t, d[0][2][0], d[0][2][2], d[0][3][0], d[0][3][2]) + sel4(t, d[1][2][0], d[1][2][2], d[1][3][0], d[1][3][2]);
        tag_st(dst, r0, tag);
        tag_st(dst + NPP * 32, r1, tag);
        TSTAMPD(23, op);
        TSTAMPD(7, __float_as_uint(r1));
    }
    auto gather = [&](int box, int per, int n) {
        const uint32_t* src = g_ll_r + (box * NPP + per * w) * 32 + lane;
        float s0, s1;
        while (true) {
            uint32_t v[11], bad = 0;
#pragma unroll
            for (int i = 0; i < 11; i++) {
                v[i] = tag;
                if (i < 8 || i < n) asm volatile("ld.relaxed.gpu.global.u32 %0, [%1];" : "=r"(v[i]) : "l"(src + i * 32) : "memory");
            }
#pragma unroll
            for (int i = 0; i < 11; i++) {
                v[i] ^= tag; bad |= v[i];
                if (i == 0) s0 = __uint_as_float(v[i]); else if (i == 1) s1 = __uint_as_float(v[i]);
                else if (i & 1) s1 += __uint_as_float(v[i]); else s0 += __uint_as_float(v[i]);
            }
            if (__all_sync(0xffffffffu, (bad & 3u) == 0)) break;
            check_timeout(t0);
        }
        sts32f(sb + SM_RQ + w * 128 + lane * 4, s0 + s1);
        TSTAMPD(r < 32 ? 26 : 27, __float_as_uint(s0));
        bar_arrive<6, 288>();
    };
#define DUMPH() do { } while (0)
    if (!is_ffn) {
        if (r >= 96) gather(r - 96, 8, 8);
        DUMPH();
        return;
    }

    uint32_t f_a[2][4][4], w2_a[4][4];
    {
        mbar_wait(bar_f, 0);
        const uint32_t fb = sb + SM_W + l_sel * 16384 + (64 * w + l_row) * 32 + ((g & 1) << 4);
#pragma unroll
        for (int j = 0; j < 2; j++)
#pragma unroll
            for (int ks = 0; ks < 4; ks++) ldsm4t(f_a[j][ks], (fb ^ (j << 4)) + ks * 512);
        mbar_wait(bar_f2, 0);
#pragma unroll
        for (int j = 0; j < 4; j++) ldsm4t(w2_a[j], (sb + SM_W + 32768 + w * 2048 + tr_off) ^ (j << 5));
    }
    {
        while (!__all_sync(0xffffffffu, ms.y == flag && ms.w == flag && mc.y == flag && mc.w == flag)) {
            ll_ld2(msrc, ms); ll_ld2(msrc + 256, mc); check_timeout(t0);
        }
        uint32_t* dst = g_ll_r + ((32 + 4 * w) * NPP + r) * 32 + t * 8 + g;
#pragma unroll
        for (int j = 0; j < 4; j++) tag_st(dst + j * NPP * 32, 0.f, tag ^ 2u);
        uint4 xv;
        xv.y = ~flag;
        ll_poll2(g_ll_x + bb * 256 + 32 * w + 2 * (lane & 15), xv, flag, t0);
        TSTAMPD(9, xv.x);
        if (r < 32) bar_arrive<7, 288>();
        const float piv = bf_lo(__shfl_sync(0xffffffffu, xv.x, lane & 16));
        const float e0 = bf_lo(xv.x) - piv, e1 = bf_hi(xv.x) - piv, e2 = bf_lo(xv.z) - piv, e3 = bf_hi(xv.z) - piv;
        float s1 = (e0 + e1) + (e2 + e3), s2 = (e0 * e0 + e1 * e1) + (e2 * e2 + e3 * e3);
#pragma unroll
        for (int of = 1; of < 16; of <<= 1) { s1 += __shfl_xor_sync(0xffffffffu, s1, of); s2 += __shfl_xor_sync(0xffffffffu, s2, of); }
        if ((lane & 15) == 0) sts64f(sb + SM_STAT + bb * 64 + w * 8, piv + s1 * (1.0f / 64.0f), s2 - s1 * s1 * (1.0f / 64.0f));
        bar_sync<1, 256>();
        float4 st[4];
#pragma unroll
        for (int i = 0; i < 4; i++) st[i] = lds128f(sb + SM_STAT + bb * 64 + i * 16);
        const float mean = (((st[0].x + st[0].z) + (st[1].x + st[1].z)) + ((st[2].x + st[2].z) + (st[3].x + st[3].z))) * 0.125f;
        const float M2 = ((st[0].y + st[0].w) + (st[1].y + st[1].w)) + ((st[2].y + st[2].w) + (st[3].y + st[3].w));
        float dv[4];
#pragma unroll
        for (int i = 0; i < 4; i++) { const float d0 = st[i].x - mean, d1 = st[i].z - mean; dv[i] = d0 * d0 + d1 * d1; }
        const float rden = ln_rden(fmaxf(M2 * (1.0f / DM) + ((dv[0] + dv[1]) + (dv[2] + dv[3])) * 0.125f, 0.f));
        TSTAMPD(24, __float_as_uint(st[3].x));
        const uint32_t m2 = pack_bf16(mean, mean);
        const uint32_t p0 = bf2_add(bf2_mul(ln_pair(xv.x, m2, rden), mc.x), ms.x);
        const uint32_t p1 = bf2_add(bf2_mul(ln_pair(xv.z, m2, rden), mc.z), ms.z);
        TSTAMPD(25, p1);
        float d[2][4][4];
#pragma unroll
        for (int ks = 0; ks < 4; ks++) {
            const uint32_t b0 = __shfl_sync(0xffffffffu, p0, 16 * (g & 1) + 4 * ks + t);
            const uint32_t b1 = __shfl_sync(0xffffffffu, p1, 16 * (g & 1) + 4 * ks + t);
#pragma unroll
            for (int j = 0; j < 2; j++) mma16816z(d[j][ks], f_a[j][ks], b0, b1);
        }
        float acc[4];
#pragma unroll
        for (int i = 0; i < 4; i++) {
            const float u0 = (d[0][0][i] + d[0][1][i]) + (d[0][2][i] + d[0][3][i]);
            const float u1 = (d[1][0][i] + d[1][1][i]) + (d[1][2][i] + d[1][3][i]);
            acc[i] = (t & 1) ? u1 : u0;
        }
        if (t < 2) sts128f(sb + SM_RGU + w * 256 + (8 * t + g) * 16, acc[0], acc[2], acc[1], acc[3]);
        bar_sync<1, 256>();
        float2 pv[8];
#pragma unroll
        for (int i = 0; i < 8; i++) pv[i] = lds64f(sb + SM_RGU + i * 256 + (lane & 15) * 16 + bb * 8);
        const float gate = bf16r(((pv[0].x + pv[1].x) + (pv[2].x + pv[3].x)) + ((pv[4].x + pv[5].x) + (pv[6].x + pv[7].x)));
        const float up   = bf16r(((pv[0].y + pv[1].y) + (pv[2].y + pv[3].y)) + ((pv[4].y + pv[5].y) + (pv[6].y + pv[7].y)));
        TSTAMPD(10, __float_as_uint(pv[7].x));
        const float hh = bf16r(silu_f(gate)) * up;
        const int sl0 = 16 * (g & 1) + 2 * t;
        const float h0 = __shfl_sync(0xffffffffu, hh, sl0), h1 = __shfl_sync(0xffffffffu, hh, sl0 + 1);
        const float h8 = __shfl_sync(0xffffffffu, hh, sl0 + 8), h9 = __shfl_sync(0xffffffffu, hh, sl0 + 9);
        const uint32_t b0 = pack_bf16(h0, h1), b1 = pack_bf16(h8, h9);
        float f[4][4];
#pragma unroll
        for (int j = 0; j < 4; j++) mma16816z(f[j], w2_a[j], b0, b1);
#pragma unroll
        for (int j = 0; j < 4; j++) tag_st(dst + j * NPP * 32, sel4(t, f[j][0], f[j][1], f[j][2], f[j][3]), tag);
        TSTAMPD(11, __float_as_uint(f[3][3]));
        if (r < 32) {
            { const uint32_t c = clk32(); while (clk32() - c < XDELAY) ; }
            gather(32 + r, 11, w < 7 ? 11 : NFFN - 77);
        }
        DUMPH();
    }
}

typedef CUresult (*EncodeFn)(CUtensorMap*, CUtensorMapDataType, cuuint32_t, void*, const cuuint64_t*, const cuuint64_t*,
                             const cuuint32_t*, const cuuint32_t*, CUtensorMapInterleave, CUtensorMapSwizzle,
                             CUtensorMapL2promotion, CUtensorMapFloatOOBfill);

void make_map(EncodeFn enc, CUtensorMap* tm, const void* ptr, uint64_t cols, uint64_t rows, uint32_t box_cols,
              uint32_t box_rows, CUtensorMapSwizzle sw, CUtensorMapL2promotion promo) {
    cuuint64_t gd[2] = {cols, rows};
    cuuint64_t gs[1] = {cols * 2};
    cuuint32_t box[2] = {box_cols, box_rows};
    cuuint32_t es[2] = {1, 1};
    enc(tm, CU_TENSOR_MAP_DATA_TYPE_BFLOAT16, 2, const_cast<void*>(ptr), gd, gs, box, es, CU_TENSOR_MAP_INTERLEAVE_NONE,
        sw, promo, CU_TENSOR_MAP_FLOAT_OOB_FILL_NONE);
}

}

extern "C" void kernel_launch(void* const* d_in, const int* in_sizes, int n_in, void* d_out, int out_size) {
    (void)in_sizes; (void)n_in; (void)out_size;
    static EncodeFn enc = nullptr;
    if (!enc) {
        cudaDriverEntryPointQueryResult qr;
        cudaGetDriverEntryPoint("cuTensorMapEncodeTiled", (void**)&enc, cudaEnableDefault, &qr);
        cudaFuncSetAttribute(fused_decode_kernel, cudaFuncAttributeMaxDynamicSharedMemorySize, SMEM_BYTES);
    }
    Maps tm;
    const CUtensorMapSwizzle S128 = CU_TENSOR_MAP_SWIZZLE_128B;
    const CUtensorMapL2promotion P256 = CU_TENSOR_MAP_L2_PROMOTION_L2_256B, P128 = CU_TENSOR_MAP_L2_PROMOTION_L2_128B;
    make_map(enc, &tm.K, d_in[1], 128, (uint64_t)64 * SK, 64, 128, S128, P128);
    make_map(enc, &tm.V, d_in[2], 128, (uint64_t)64 * SK, 64, 128, S128, P128);
    make_map(enc, &tm.Wq, d_in[3], 4096, 512, 64, 128, S128, P256);
    make_map(enc, &tm.Wo, d_in[4], 512, 4096, 64, 64, S128, P256);
    make_map(enc, &tm.W2, d_in[8], 512, FF, 64, 16, S128, P256);
    make_map(enc, &tm.Wm, d_in[10], 6 * DM, 512, 8, 256, CU_TENSOR_MAP_SWIZZLE_NONE, P128);
    make_map(enc, &tm.Wm16, d_in[10], 6 * DM, 512, 16, 256, CU_TENSOR_MAP_SWIZZLE_32B, P128);
    make_map(enc, &tm.W1, d_in[6], FF, 512, 16, 256, CU_TENSOR_MAP_SWIZZLE_32B, P128);
    make_map(enc, &tm.W3, d_in[7], FF, 512, 16, 256, CU_TENSOR_MAP_SWIZZLE_32B, P128);
    fused_decode_kernel<<<NCTA, NTHREADS, SMEM_BYTES>>>(
        (const bf16*)d_in[0], (const bf16*)d_in[9], (const bf16*)d_in[2], (const bf16*)d_in[10], (const bf16*)d_in[6],
        (const bf16*)d_in[7], (const bf16*)d_in[8], (bf16*)d_out, tm);
}
```

```cpp
#include <cuda_runtime.h>
#include <cuda.h>
#include <cuda_bf16.h>
#include <stdint.h>

namespace {

typedef __nv_bfloat16 bf16;
typedef unsigned long long u64;

constexpr int DM   = 512;
constexpr int SK   = 16384;
constexpr int WIN  = 4096;
constexpr int FF   = 1376;
constexpr int NCTA = 128;
constexpr int NFFN = 86;
constexpr int NPP  = 88;
constexpr int NS   = 7;
constexpr int TILE = 16384;
#define BURST 5
#define NPF 3
#define FSTEADY 4
#define RELD 5
#define HDELAY 2400u
#define XDELAY 300u
#define PF_J 35
#define PF_J2 32
#define PF_MASK 0
#define VD 7
#define VDEPTH 46
#define SPARE 1
#define KLAG 2
#define POLL_REM 4
#define TH_MUL 0
#define THETA 1
constexpr int NTHREADS = 320;

constexpr int SM_W    = 0;
constexpr int SM_RING = 65536;
constexpr int SM_SCO  = SM_RING + NS * TILE;
constexpr int SM_SCR  = SM_SCO + 16384;
constexpr int SM_P    = SM_SCR + 16384;
constexpr int SM_RMOD = SM_P + 8192;
constexpr int SM_RQ   = SM_RMOD + 512;
constexpr int SM_RO   = SM_RQ + 2048;
constexpr int SM_RGU  = SM_RO + 2048;
constexpr int SM_SILU = SM_RGU + 2048;
constexpr int SM_STAT = SM_SILU + 2048;
constexpr int SM_SMAX = SM_STAT + 128;
constexpr int SM_SSUM = SM_SMAX + 32;
constexpr int SM_SCNT = SM_SSUM + 32;
constexpr int SM_BAR  = SM_SCNT + 32;
constexpr int SM_HIST = SM_BAR + 8 * (2 * NS + 14);
constexpr int SM_END  = SM_HIST;
static_assert(VD * 2048 * 8 <= NS * TILE, "V rings");
constexpr int SMEM_BYTES = SM_END + 1024;
static_assert(SMEM_BYTES <= 232448, "smem");

__device__ unsigned int g_epoch;
__device__ __align__(128) u64 g_ll_x[2 * 256];
__device__ __align__(128) u64 g_ll_m[2 * 6 * 256];
__device__ __align__(128) uint32_t g_ll_r[2 * 32 * NPP * 32];
#define THIST(wgt) do { } while (0)
#define TSTAMP(i) do { } while (0)
#define TSTAMPD(i, dep) do { } while (0)

__device__ __forceinline__ uint32_t smem_u32(const void* p) { return (uint32_t)__cvta_generic_to_shared(p); }
__device__ __forceinline__ uint32_t pack_bf16(float lo, float hi) {
    uint32_t r; asm("cvt.rn.bf16x2.f32 %0, %1, %2;" : "=r"(r) : "f"(hi), "f"(lo)); return r;
}
__device__ __forceinline__ float bf16r(float v) { return __uint_as_float(pack_bf16(0.0f, v)); }
__device__ __forceinline__ float bf_lo(uint32_t v) { return __uint_as_float(v << 16); }
__device__ __forceinline__ float bf_hi(uint32_t v) { return __uint_as_float(v & 0xffff0000u); }
__device__ __forceinline__ uint32_t bf2_mul(uint32_t a, uint32_t b) { uint32_t r; asm("mul.rn.bf16x2 %0, %1, %2;" : "=r"(r) : "r"(a), "r"(b)); return r; }
__device__ __forceinline__ uint32_t bf2_add(uint32_t a, uint32_t b) { uint32_t r; asm("add.rn.bf16x2 %0, %1, %2;" : "=r"(r) : "r"(a), "r"(b)); return r; }
__device__ __forceinline__ uint32_t bf2_sub(uint32_t a, uint32_t b) { uint32_t r; asm("sub.rn.bf16x2 %0, %1, %2;" : "=r"(r) : "r"(a), "r"(b)); return r; }
__device__ __forceinline__ float ex2_fast(float v) { float r; asm("ex2.approx.ftz.f32 %0, %1;" : "=f"(r) : "f"(v)); return r; }
__device__ __forceinline__ float ex2_sub(float v) { float r; asm("ex2.approx.f32 %0, %1;" : "=f"(r) : "f"(v)); return r; }
__device__ __forceinline__ float sqrt_fast(float v) { float r; asm("sqrt.approx.ftz.f32 %0, %1;" : "=f"(r) : "f"(v)); return r; }
__device__ __forceinline__ float rcp_fast(float v) { float r; asm("rcp.approx.ftz.f32 %0, %1;" : "=f"(r) : "f"(v)); return r; }
constexpr float LOG2E = 1.4426950408889634f;
__device__ __forceinline__ float silu_f(float v) { return v * rcp_fast(1.0f + ex2_fast(-LOG2E * v)); }
__device__ __forceinline__ float score_round(float v) { return bf16r(bf16r(v) * 0.08838834764831845f); }
__device__ __forceinline__ float warp_max(float v) {
    int i = __float_as_int(v);
    i ^= (i >> 31) & 0x7fffffff;
    i = __reduce_max_sync(0xffffffffu, i);
    i ^= (i >> 31) & 0x7fffffff;
    return __int_as_float(i);
}
__device__ __forceinline__ float ln_rden(float var) { return rcp_fast(bf16r(sqrt_fast(bf16r(bf16r(var) + 1e-5f)))); }
__device__ __forceinline__ uint32_t ln_pair(uint32_t x2, uint32_t m2, float rden) {
    const uint32_t d = bf2_sub(x2, m2);
    return pack_bf16(bf_lo(d) * rden, bf_hi(d) * rden);
}

__device__ __forceinline__ void mbar_init(uint32_t bar, uint32_t cnt) {
    asm volatile("mbarrier.init.shared::cta.b64 [%0], %1;" :: "r"(bar), "r"(cnt) : "memory");
}
__device__ __forceinline__ void mbar_expect_tx(uint32_t bar, uint32_t bytes) {
    asm volatile("mbarrier.arrive.expect_tx.shared::cta.b64 _, [%0], %1;" :: "r"(bar), "r"(bytes) : "memory");
}
__device__ __forceinline__ void mbar_arrive(uint32_t bar) {
    asm volatile("mbarrier.arrive.shared::cta.b64 _, [%0];" :: "r"(bar) : "memory");
}
__device__ __forceinline__ uint32_t clk32() { uint32_t c; asm volatile("mov.u32 %0, %%clock;" : "=r"(c)); return c; }
__device__ __forceinline__ void check_timeout(uint32_t t0) { if ((int32_t)(clk32() - t0) < 0) __trap(); }
#define MBAR_WAIT_ASM(SEM) \
    asm volatile("{\n.reg .pred p;\n.reg .s32 t1;\n" \
                 "W_%=:\n" \
                 "mbarrier.try_wait.parity" SEM ".shared::cta.b64 p, [%0], %1;\n@p bra D_%=;\n" \
                 "mov.u32 t1, %%clock;\nsub.s32 t1, t1, %2;\nsetp.ge.s32 p, t1, 0;\n@p bra W_%=;\ntrap;\n" \
                 "D_%=:\n}" :: "r"(bar), "r"(parity), "r"(t0) : "memory")
__device__ __forceinline__ void mbar_wait_t(uint32_t bar, uint32_t parity, uint32_t t0) { MBAR_WAIT_ASM(""); }
__device__ __forceinline__ void mbar_wait_cluster_t(uint32_t bar, uint32_t parity, uint32_t t0) { MBAR_WAIT_ASM(".acquire.cluster"); }
#define mbar_wait(bar, parity) mbar_wait_t(bar, parity, t0)
#define mbar_wait_cluster(bar, parity) mbar_wait_cluster_t(bar, parity, t0)
__device__ __forceinline__ bool mbar_test(uint32_t bar, uint32_t parity) {
    uint32_t ok;
    asm volatile("{\n.reg .pred p;\nmbarrier.test_wait.parity.shared::cta.b64 p, [%1], %2;\nselp.u32 %0, 1, 0, p;\n}"
                 : "=r"(ok) : "r"(bar), "r"(parity) : "memory");
    return ok != 0;
}
__device__ __forceinline__ bool elect_one() {
    uint32_t p;
    asm volatile("{\n.reg .pred P;\nelect.sync _|P, 0xffffffff;\nselp.u32 %0, 1, 0, P;\n}" : "=r"(p));
    return p != 0;
}
__device__ __forceinline__ void tma2d(uint32_t dst, const CUtensorMap* tm, int c0, int c1, uint32_t bar) {
    asm volatile("cp.async.bulk.tensor.2d.shared::cluster.global.mbarrier::complete_tx::bytes [%0], [%1, {%3, %4}], [%2];"
                 :: "r"(dst), "l"(tm), "r"(bar), "r"(c0), "r"(c1) : "memory");
}
__device__ __forceinline__ void tma_pf(const CUtensorMap* tm, int c0, int c1) {
    asm volatile("cp.async.bulk.prefetch.tensor.2d.L2.global.tile [%0, {%1, %2}];" :: "l"(tm), "r"(c0), "r"(c1) : "memory");
}
__device__ __forceinline__ void bulk_pf(const void* p, uint32_t bytes) {
    asm volatile("cp.async.bulk.prefetch.L2.global [%0], %1;" :: "l"(p), "r"(bytes) : "memory");
}
__device__ __forceinline__ void tma2d_ef(uint32_t dst, const CUtensorMap* tm, int c0, int c1, uint32_t bar, u64 pol) {
    asm volatile("cp.async.bulk.tensor.2d.shared::cluster.global.mbarrier::complete_tx::bytes.L2::cache_hint [%0], [%1, {%3, %4}], [%2], %5;"
                 :: "r"(dst), "l"(tm), "r"(bar), "r"(c0), "r"(c1), "l"(pol) : "memory");
}
__device__ __forceinline__ void ldsm2t(uint32_t& a0, uint32_t& a1, uint32_t addr) {
    asm volatile("ldmatrix.sync.aligned.m8n8.x2.trans.shared.b16 {%0,%1}, [%2];" : "=r"(a0), "=r"(a1) : "r"(addr) : "memory");
}
__device__ __forceinline__ void ldsm4(uint32_t (&a)[4], uint32_t addr) {
    asm volatile("ldmatrix.sync.aligned.m8n8.x4.shared.b16 {%0,%1,%2,%3}, [%4];"
                 : "=r"(a[0]), "=r"(a[1]), "=r"(a[2]), "=r"(a[3]) : "r"(addr) : "memory");
}
__device__ __forceinline__ void ldsm4t(uint32_t (&a)[4], uint32_t addr) {
    asm volatile("ldmatrix.sync.aligned.m8n8.x4.trans.shared.b16 {%0,%1,%2,%3}, [%4];"
                 : "=r"(a[0]), "=r"(a[1]), "=r"(a[2]), "=r"(a[3]) : "r"(addr) : "memory");
}
__device__ __forceinline__ void mma16816(float (&d)[4], const uint32_t (&a)[4], uint32_t b0, uint32_t b1) {
    asm volatile("mma.sync.aligned.m16n8k16.row.col.f32.bf16.bf16.f32 {%0,%1,%2,%3}, {%4,%5,%6,%7}, {%8,%9}, {%0,%1,%2,%3};"
                 : "+f"(d[0]), "+f"(d[1]), "+f"(d[2]), "+f"(d[3])
                 : "r"(a[0]), "r"(a[1]), "r"(a[2]), "r"(a[3]), "r"(b0), "r"(b1));
}
__device__ __forceinline__ void mma16816z(float (&d)[4], const uint32_t (&a)[4], uint32_t b0, uint32_t b1) {
    asm volatile("mma.sync.aligned.m16n8k16.row.col.f32.bf16.bf16.f32 {%0,%1,%2,%3}, {%4,%5,%6,%7}, {%8,%9}, {%10,%10,%10,%10};"
                 : "=f"(d[0]), "=f"(d[1]), "=f"(d[2]), "=f"(d[3])
                 : "r"(a[0]), "r"(a[1]), "r"(a[2]), "r"(a[3]), "r"(b0), "r"(b1), "f"(0.0f));
}
template <int ID, int N> __device__ __forceinline__ void bar_sync() { asm volatile("bar.sync %0, %1;" :: "n"(ID), "n"(N) : "memory"); }
template <int ID, int N> __device__ __forceinline__ void bar_arrive() { asm volatile("bar.arrive %0, %1;" :: "n"(ID), "n"(N) : "memory"); }
__device__ __forceinline__ void cluster_arrive_relaxed() { asm volatile("barrier.cluster.arrive.relaxed.aligned;" ::: "memory"); }
__device__ __forceinline__ void cluster_wait() { asm volatile("barrier.cluster.wait.acquire.aligned;" ::: "memory"); }

__device__ __forceinline__ void sts32f(uint32_t a, float v) { asm volatile("st.shared.f32 [%0], %1;" :: "r"(a), "f"(v) : "memory"); }
__device__ __forceinline__ void sts32(uint32_t a, uint32_t v) { asm volatile("st.shared.b32 [%0], %1;" :: "r"(a), "r"(v) : "memory"); }
__device__ __forceinline__ uint32_t lds32(uint32_t a) { uint32_t v; asm volatile("ld.shared.b32 %0, [%1];" : "=r"(v) : "r"(a) : "memory"); return v; }
__device__ __forceinline__ float2 lds64f(uint32_t a) { float2 v; asm volatile("ld.shared.v2.f32 {%0,%1}, [%2];" : "=f"(v.x), "=f"(v.y) : "r"(a) : "memory"); return v; }
__device__ __forceinline__ float4 lds128f(uint32_t a) { float4 v; asm volatile("ld.shared.v4.f32 {%0,%1,%2,%3}, [%4];" : "=f"(v.x), "=f"(v.y), "=f"(v.z), "=f"(v.w) : "r"(a) : "memory"); return v; }
__device__ __forceinline__ void lds64(uint32_t& x, uint32_t& y, uint32_t a) { asm volatile("ld.shared.v2.b32 {%0,%1}, [%2];" : "=r"(x), "=r"(y) : "r"(a) : "memory"); }
__device__ __forceinline__ void lds128(uint32_t* v, uint32_t a) { asm volatile("ld.shared.v4.b32 {%0,%1,%2,%3}, [%4];" : "=r"(v[0]), "=r"(v[1]), "=r"(v[2]), "=r"(v[3]) : "r"(a) : "memory"); }
__device__ __forceinline__ void sts64f(uint32_t a, float x, float y) { asm volatile("st.shared.v2.f32 [%0], {%1,%2};" :: "r"(a), "f"(x), "f"(y) : "memory"); }
__device__ __forceinline__ void sts64(uint32_t a, uint32_t x, uint32_t y) { asm volatile("st.shared.v2.b32 [%0], {%1,%2};" :: "r"(a), "r"(x), "r"(y) : "memory"); }
__device__ __forceinline__ void sts128(uint32_t a, uint32_t x, uint32_t y, uint32_t z, uint32_t w) { asm volatile("st.shared.v4.b32 [%0], {%1,%2,%3,%4};" :: "r"(a), "r"(x), "r"(y), "r"(z), "r"(w) : "memory"); }
__device__ __forceinline__ void sts128f(uint32_t a, float x, float y, float z, float w) { asm volatile("st.shared.v4.f32 [%0], {%1,%2,%3,%4};" :: "r"(a), "f"(x), "f"(y), "f"(z), "f"(w) : "memory"); }

__device__ __forceinline__ void ll_st(u64* p, uint32_t lo, uint32_t hi) {
    asm volatile("{\n.reg .b64 v;\nmov.b64 v, {%1, %2};\nst.relaxed.gpu.global.b64 [%0], v;\n}" :: "l"(p), "r"(lo), "r"(hi) : "memory");
}
__device__ __forceinline__ void ll_ld2(const u64* p, uint4& v) {
    asm volatile("{\n.reg .b64 a, b;\nld.relaxed.gpu.global.v2.b64 {a, b}, [%4];\nmov.b64 {%0, %1}, a;\nmov.b64 {%2, %3}, b;\n}"
                 : "=r"(v.x), "=r"(v.y), "=r"(v.z), "=r"(v.w) : "l"(p) : "memory");
}
__device__ __forceinline__ void ll_poll2(const u64* p, uint4& v, uint32_t flag, uint32_t t0) {
    while (!__all_sync(0xffffffffu, v.y == flag && v.w == flag)) { ll_ld2(p, v); check_timeout(t0); }
}
__device__ __forceinline__ void tag_st(uint32_t* p, float v, uint32_t tag) {
    asm volatile("st.relaxed.gpu.global.u32 [%0], %1;" :: "l"(p), "r"((__float_as_uint(v) & ~3u) | tag) : "memory");
}
__device__ __forceinline__ float sel4(int t, float a, float b, float c, float d) {
    float lo = (t & 1) ? b : a, hi = (t & 1) ? d : c;
    return (t & 2) ? hi : lo;
}

struct Maps { CUtensorMap K, V, Wq, Wo, W2, Wm, W1, W3, Wm16; };

__global__ void __cluster_dims__(2, 1, 1) __launch_bounds__(NTHREADS, 1)
fused_decode_kernel(const bf16* __restrict__ x, const bf16* __restrict__ cvec, const bf16* __restrict__ vcache,
                    const bf16* __restrict__ wmod, const bf16* __restrict__ w1p, const bf16* __restrict__ w3p, const bf16* __restrict__ w2p,
                    bf16* __restrict__ out, const __grid_constant__ Maps tm)
{
    extern __shared__ uint8_t smem_raw[];
    const uint32_t sb = (smem_u32(smem_raw) + 1023u) & ~1023u;
    const int tid = threadIdx.x, lane = tid & 31;
    const int warp = __shfl_sync(0xffffffffu, tid >> 5, 0);
    const uint32_t t0 = clk32();
    const int r = blockIdx.x;
    const int half = r & 1, b = r >> 6, cg = r & 63;
    const int g = lane >> 2, t = lane & 3;
    const uint32_t bar_w = sb + SM_BAR, bar_full = bar_w + 32;
    const uint32_t bar_f = bar_full + 8 * NS + 8, bar_m = bar_f + 8, bar_wfree = bar_m + 8, bar_go = bar_wfree + 8, bar_empty = bar_go + 8;
    const uint32_t bar_f2 = bar_empty + 8 * NS, bar_sc = bar_f2 + 8;
    const bool is_ffn = r < NFFN;
    const uint32_t l_row = (lane & 7) + 8 * (lane >> 4);
    const uint32_t l_sel = (lane >> 3) & 1;

    if (warp == 8) {
        const bool el = elect_one();
        const int kv_row0 = (r >> 1) * SK + (SK - WIN);
        u64 pol;
        asm volatile("createpolicy.fractional.L2::evict_first.b64 %0, 1.0;" : "=l"(pol));
        if (el) {
            TSTAMP(0);
            mbar_init(bar_m, 1);
#pragma unroll
            for (int i = 0; i < BURST; i++) mbar_init(bar_w + 8 * i, 1);
            asm volatile("fence.mbarrier_init.release.cluster;" ::: "memory");
            mbar_expect_tx(bar_m, 8192);
            tma2d(sb + SM_P, &tm.Wm, r * 8, 0, bar_m);
            tma2d(sb + SM_P + 4096, &tm.Wm, r * 8, 256, bar_m);
#pragma unroll
            for (int i = 0; i < BURST; i++) {
                mbar_expect_tx(bar_w + 8 * i, TILE);
                if (i < 4) tma2d(sb + i * TILE, &tm.Wq, cg * 64, i * 128, bar_w + 8 * i);
                else       tma2d_ef(sb + i * TILE, &tm.K, half * 64, kv_row0 + (i - 4) * 128, bar_w + 8 * i, pol);
            }
            TSTAMP(8);
#pragma unroll
            for (int i = BURST; i < 2 * NS + 14; i++) if (i != NS + 6) mbar_init(bar_w + 8 * i, ((i < NS + 9 && i != NS + 7) || i >= 2 * NS + 9) ? 1 : 8);
            asm volatile("fence.mbarrier_init.release.cluster;" ::: "memory");
#pragma unroll
            for (int i = 0; i < 4; i++) mbar_expect_tx(bar_sc + 8 * i, 4096);
        }
        __syncwarp();
        cluster_arrive_relaxed();
#pragma unroll 1
        for (int u = BURST; u < 4 + NS + NPF; u++) {
            const uint32_t gb = bar_w + 8 * (u >= BURST + 2 ? u - (BURST - 2) : 2 * (u - BURST) + 1);
            bool rel;
            while (!((rel = mbar_test(bar_empty, 0)) && (u >= 4 + NS || mbar_test(bar_w + 8 * (u - RELD), 0))) && !mbar_test(gb, 0)) check_timeout(t0);
            if (u < 4 + NS) {
                if (el) {
                    mbar_expect_tx(bar_w + 8 * u, TILE);
                    tma2d_ef(sb + u * TILE, &tm.K, half * 64, kv_row0 + (u - 4) * 128, bar_w + 8 * u, pol);
                }
            } else {
                if (rel) break;
                if (el) asm volatile("cp.async.bulk.prefetch.tensor.2d.L2.global.tile [%0, {%1, %2}];"
                                     :: "l"(&tm.K), "r"(half * 64), "r"(kv_row0 + (u - 4) * 128) : "memory");
            }
        }
        int slot = 0, gslot = NS - FSTEADY;
        uint32_t ph = 0, gph = 0;
#pragma unroll 1
        for (int j = NS; j < 36; j++) {
            if (j == PF_J && el) {
#pragma unroll
                for (int i = 0; i < 4; i++) bulk_pf(reinterpret_cast<const char*>(wmod) + (size_t)(4 * r + i) * (6 * DM * 2) + 2 * DM * 2, 4 * DM * 2);
            }
            if (j == PF_J2 && el) {
                if (PF_MASK & 2) bulk_pf(reinterpret_cast<const char*>(w1p) + r * (FF * DM * 2 / NCTA), FF * DM * 2 / NCTA);
                if (PF_MASK & 4) bulk_pf(reinterpret_cast<const char*>(w3p) + r * (FF * DM * 2 / NCTA), FF * DM * 2 / NCTA);
                if (PF_MASK & 8) bulk_pf(reinterpret_cast<const char*>(w2p) + r * (FF * DM * 2 / NCTA), FF * DM * 2 / NCTA);
            }
            if (j < 32) mbar_wait(bar_empty + 8 * slot, ph);
            if (FSTEADY < NS) {
                mbar_wait(bar_full + 8 * gslot, gph);
                if (++gslot == NS) { gslot = 0; gph ^= 1u; }
            }
            if (j < 32) {
                if (el) {
                    mbar_expect_tx(bar_full + 8 * slot, TILE);
                    tma2d_ef(sb + SM_RING + slot * TILE, &tm.K, half * 64, kv_row0 + j * 128, bar_full + 8 * slot, pol);
                }
                if (++slot == NS) { slot = 0; ph ^= 1u; }
            } else if (el) {
                const int i = 2 * (j - 32);
                mbar_expect_tx(bar_w + 4 * i, TILE);
                tma2d(sb + SM_W + i * 8192, &tm.Wo, i * 64, cg * 64, bar_w + 4 * i);
                tma2d(sb + SM_W + i * 8192 + 8192, &tm.Wo, i * 64 + 64, cg * 64, bar_w + 4 * i);
            }
        }
        if (el) TSTAMP(17);
        mbar_wait(bar_wfree, 0);
        if (el) {
            mbar_expect_tx(bar_m, 16384);
            tma2d(sb + SM_W + 49152, &tm.Wm16, 2 * DM + r * 16, 0, bar_m);
            tma2d(sb + SM_W + 49152 + 8192, &tm.Wm16, 2 * DM + r * 16, 256, bar_m);
        }
        if (is_ffn) {
            mbar_wait(bar_go, 0);
            if (el) TSTAMP(18);
            if (el) {
                mbar_expect_tx(bar_f, 32768);
#pragma unroll 1
                for (int i = 0; i < 4; i++) tma2d(sb + SM_W + i * 8192, i < 2 ? &tm.W1 : &tm.W3, r * 16, (i & 1) * 256, bar_f);
                mbar_expect_tx(bar_f2, TILE);
#pragma unroll 1
                for (int i = 0; i < 8; i++) tma2d(sb + SM_W + 32768 + i * 2048, &tm.W2, i * 64, r * 16, bar_f2);
            }
        }
        cluster_wait();
        return;
    }

    uint32_t flag;
    asm volatile("ld.relaxed.gpu.global.u32 %0, [%1];" : "=r"(flag) : "l"(&g_epoch) : "memory");

    if (warp == 9) {
        const uint4* xp = reinterpret_cast<const uint4*>(x + b * DM);
        const uint4 xa = __ldg(xp + lane), xb = __ldg(xp + 32 + lane);
        cluster_arrive_relaxed();
        flag += 1u;
        const uint32_t xw[8] = {xa.x, xa.y, xa.z, xa.w, xb.x, xb.y, xb.z, xb.w};
        float s = 0.f;
#pragma unroll
        for (int i = 0; i < 8; i++) s += bf_lo(xw[i]) + bf_hi(xw[i]);
#pragma unroll 1
        for (int o = 16; o > 0; o >>= 1) s += __shfl_xor_sync(0xffffffffu, s, o);
        const float mean = s * (1.0f / DM);
        float m2 = 0.f;
#pragma unroll
        for (int i = 0; i < 8; i++) { const float d0 = bf_lo(xw[i]) - mean, d1 = bf_hi(xw[i]) - mean; m2 += d0 * d0; m2 += d1 * d1; }
#pragma unroll 1
        for (int o = 16; o > 0; o >>= 1) m2 += __shfl_xor_sync(0xffffffffu, m2, o);
        {
            const uint32_t mm = pack_bf16(mean, mean);
            const float rden = ln_rden(m2 * (1.0f / DM));
            sts128(sb + SM_RO + lane * 16, ln_pair(xa.x, mm, rden), ln_pair(xa.y, mm, rden), ln_pair(xa.z, mm, rden), ln_pair(xa.w, mm, rden));
            sts128(sb + SM_RO + 512 + lane * 16, ln_pair(xb.x, mm, rden), ln_pair(xb.y, mm, rden), ln_pair(xb.z, mm, rden), ln_pair(xb.w, mm, rden));
        }
        const int fpos = (cg >> 1) * 8 + 2 * t + (cg & 1);
        if (lane == 0) TSTAMP(19);
        bar_sync<2, 288>();
        {
            float4 v = lds128f(sb + SM_RMOD + g * 64 + t * 16);
#pragma unroll
            for (int o = 4; o < 32; o <<= 1) {
                v.x += __shfl_xor_sync(0xffffffffu, v.x, o); v.y += __shfl_xor_sync(0xffffffffu, v.y, o);
                v.z += __shfl_xor_sync(0xffffffffu, v.z, o); v.w += __shfl_xor_sync(0xffffffffu, v.w, o);
            }
            uint32_t m = g ? pack_bf16(v.y, v.w) : pack_bf16(v.x, v.z);
            if (b) m = bf2_add(m, 0x3f803f80u);
            if (lane < 8) ll_st(&g_ll_m[(g * 6 + b) * 256 + fpos], m, flag);
        }
        if (lane == 0) TSTAMP(1);
        cluster_wait();

        {
            float d[2][4];
#pragma unroll
            for (int i = 0; i < 4; i++) { d[0][i] = d[1][i] = 0.f; }
            mbar_wait(bar_m, 1);
            const uint32_t base = sb + SM_W + 49152 + l_row * 32 + ((l_sel ^ (g & 1)) << 4);
            const uint32_t sa = sb + SM_SILU + (g & 1) * 1024 + t * 4;
#pragma unroll 1
            for (int ks = 0; ks < 32; ks += 2) {
                uint32_t a0[4], a1[4];
                ldsm4t(a0, base + ks * 512);
                ldsm4t(a1, base + ks * 512 + 512);
                mma16816(d[0], a0, lds32(sa + ks * 32), lds32(sa + ks * 32 + 16));
                mma16816(d[1], a1, lds32(sa + ks * 32 + 32), lds32(sa + ks * 32 + 48));
            }
            const uint32_t p0 = pack_bf16(d[0][0] + d[1][0], d[0][2] + d[1][2]), p1 = pack_bf16(d[0][1] + d[1][1], d[0][3] + d[1][3]);
            const uint32_t a0 = __shfl_sync(0xffffffffu, p0, 8 * t), a1 = __shfl_sync(0xffffffffu, p0, 8 * t + 4);
            const uint32_t c0 = __shfl_sync(0xffffffffu, p1, 8 * t), c1 = __shfl_sync(0xffffffffu, p1, 8 * t + 4);
            uint32_t m = __byte_perm((g & 2) ? c0 : a0, (g & 2) ? c1 : a1, (g & 1) ? 0x7632 : 0x5410);
            if ((r >> 5) == 2) m = bf2_add(m, 0x3f803f80u);
            if (lane < 16) ll_st(&g_ll_m[((g >> 1) * 6 + 2) * 256 + r * 8 + 2 * t + (g & 1)], m, flag);
            if (lane == 0) TSTAMP(13);
        }

        bar_sync<4, 288>();
        if (is_ffn) {
            const uint32_t* base = g_ll_r + ((r & 31) * NPP + lane) * 32;
            while (true) {
                uint32_t v0, v1;
                asm volatile("ld.relaxed.gpu.global.u32 %0, [%1];" : "=r"(v0) : "l"(base) : "memory");
                asm volatile("ld.relaxed.gpu.global.u32 %0, [%1];" : "=r"(v1) : "l"(base + 1024) : "memory");
                const int cnt = __popc(__ballot_sync(0xffffffffu, ((v0 ^ flag) & 3u) == 0)) + __popc(__ballot_sync(0xffffffffu, ((v1 ^ flag) & 3u) == 0));
                if (cnt >= THETA + TH_MUL * ((r >> 1) & 7)) break;
                __nanosleep(200);
                check_timeout(t0);
            }
            if (lane == 0) mbar_arrive(bar_go);
        }
        if (r >= 32 && r < 96) return;
        const bool fin = r < 32;
        const int fb = fin ? (lane >> 3) & 1 : (r >> 4) & 1;
        const int col = fin ? r * 16 + (lane >> 4) * 8 + (lane & 7) : (r & 15) * 32 + lane;
        const int wi = (col >> 4) * 8 + (col & 6) + ((col >> 3) & 1);
        u64 gw, xq;
        while (true) {
            asm volatile("ld.relaxed.gpu.global.b64 %0, [%1];" : "=l"(gw) : "l"(&g_ll_m[(fb * 6 + (fin ? 5 : 2)) * 256 + wi]) : "memory");
            if (__all_sync(0xffffffffu, (uint32_t)(gw >> 32) == flag)) break;
            check_timeout(t0);
        }
        if (fin) {
            bar_sync<7, 288>();
            while (true) {
                asm volatile("ld.relaxed.gpu.global.b64 %0, [%1];" : "=l"(xq) : "l"(&g_ll_x[fb * 256 + wi]) : "memory");
                if (__all_sync(0xffffffffu, (uint32_t)(xq >> 32) == flag)) break;
                check_timeout(t0);
            }
        } else {
            xq = __ldg(reinterpret_cast<const uint32_t*>(x + fb * DM) + (col >> 1));
        }
        const float xin = (lane & 1) ? bf_hi((uint32_t)xq) : bf_lo((uint32_t)xq);
        const float gt = (lane & 1) ? bf_hi((uint32_t)gw) : bf_lo((uint32_t)gw);
        sts32f(sb + SM_RMOD + lane * 4, xin + gt);
        bar_sync<6, 288>();
        float v[8];
#pragma unroll
        for (int i = 0; i < 8; i++) v[i] = __uint_as_float(lds32(sb + SM_RQ + i * 128 + lane * 4));
        const float res = xin + bf16r(gt * bf16r(((v[0] + v[1]) + (v[2] + v[3])) + ((v[4] + v[5]) + (v[6] + v[7]))));
        const uint32_t pr = pack_bf16(res, __shfl_down_sync(0xffffffffu, res, 1));
        if (!(lane & 1)) {
            if (fin) reinterpret_cast<uint32_t*>(out)[(fb * DM + col) >> 1] = pr;
            else ll_st(&g_ll_x[fb * 256 + wi], pr, flag);
        }
        TSTAMPD(fin ? 12 : 14, pr);
        if (r == 0 && lane == 0) asm volatile("st.relaxed.gpu.global.u32 [%0], %1;" :: "l"(&g_epoch), "r"(flag) : "memory");
        return;
    }

    const int w = warp;
    {
        const uint32_t* cp = reinterpret_cast<const uint32_t*>(cvec + 64 * w) + lane;
        const uint32_t c0 = __ldg(cp), c1 = __ldg(cp + DM / 2);
        cluster_arrive_relaxed();
        sts32(sb + SM_SILU + w * 128 + lane * 4, pack_bf16(silu_f(bf_lo(c0)), silu_f(bf_hi(c0))));
        sts32(sb + SM_SILU + 1024 + w * 128 + lane * 4, pack_bf16(silu_f(bf_lo(c1)), silu_f(bf_hi(c1))));
        cluster_wait();
        __syncwarp();
        uint32_t sc[8];
#pragma unroll
        for (int i = 0; i < 8; i++) sc[i] = lds32(sb + SM_SILU + (g & 1) * 1024 + w * 128 + i * 16 + t * 4);
        mbar_wait(bar_m, 0);
        if (tid == 0) TSTAMP(15);
        float d[2][4];
        uint32_t a[4][4];
#pragma unroll
        for (int ks = 0; ks < 4; ks++) {
            ldsm2t(a[ks][0], a[ks][2], sb + SM_P + (64 * w + 16 * ks + (lane & 15)) * 16);
            a[ks][1] = a[ks][3] = 0u;
        }
        mma16816z(d[0], a[0], sc[0], sc[1]); mma16816z(d[1], a[1], sc[2], sc[3]);
        mma16816(d[0], a[2], sc[4], sc[5]);  mma16816(d[1], a[3], sc[6], sc[7]);
        if (t == 0) sts64f(sb + SM_RMOD + w * 64 + g * 8, d[0][0] + d[1][0], d[0][1] + d[1][1]);
        bar_sync<2, 288>();
    }
    flag += 1u;

    const uint32_t tr_off = l_row * 128 + ((l_sel ^ (lane & 7)) << 4);
    const uint32_t red_st = (w * 64 + 16 * t + g) * 4;
    uint32_t qf[8];
    {
        const uint32_t lnp = sb + SM_RO + (32 * w + 8 * ((lane >> 2) & 3) + t) * 4;
        const uint32_t ln0 = lds32(lnp), ln1 = lds32(lnp + 16);
        uint4 hv; hv.y = ~flag;
        { const uint32_t c = clk32(); while (clk32() - c < HDELAY) ; }
        ll_poll2(g_ll_m + (b * 6 + (lane >> 4)) * 256 + 32 * w + 2 * (lane & 15), hv, flag, t0);
        uint32_t a[4][4][4];
        mbar_wait(bar_w + 8 * (w >> 1), 0);
        const uint32_t base = sb + SM_W + w * 8192 + tr_off;
#pragma unroll
        for (int j = 0; j < 4; j++)
#pragma unroll
            for (int ks = 0; ks < 4; ks++) ldsm4t(a[ks][j], (base ^ (j << 5)) + ks * 2048);
        if (tid == 0) TSTAMP(2);
        hv.x = bf2_add(bf2_mul(ln0, __shfl_down_sync(0xffffffffu, hv.x, 16)), hv.x);
        hv.z = bf2_add(bf2_mul(ln1, __shfl_down_sync(0xffffffffu, hv.z, 16)), hv.z);
        float d[4][4];
#pragma unroll
        for (int ks = 0; ks < 4; ks++) {
            const uint32_t b0 = __shfl_sync(0xffffffffu, hv.x, 4 * ks + t);
            const uint32_t b1 = __shfl_sync(0xffffffffu, hv.z, 4 * ks + t);
#pragma unroll
            for (int j = 0; j < 4; j++) { if (ks == 0) mma16816z(d[j], a[ks][j], b0, b1); else mma16816(d[j], a[ks][j], b0, b1); }
        }
        sts32f(sb + SM_RQ + red_st, sel4(t, d[0][0], d[1][0], d[2][0], d[3][0]));
        sts32f(sb + SM_RQ + red_st + 32, sel4(t, d[0][2], d[1][2], d[2][2], d[3][2]));
        bar_sync<1, 256>();
        float q0 = 0.f, q1 = 0.f;
#pragma unroll
        for (int i = 0; i < 8; i++) { float2 v = lds64f(sb + SM_RQ + i * 256 + lane * 8); q0 += v.x; q1 += v.y; }
        const uint32_t qp = pack_bf16(q0, q1);
#pragma unroll
        for (int i = 0; i < 8; i++) qf[i] = __shfl_sync(0xffffffffu, qp, 4 * i + t);
        if (tid == 0) TSTAMP(3);
    }

    int slot = 0;
    uint32_t ph = 0;
    const float ZERO_P = -92.93f;
    const uint32_t lst = sb + SM_SCO;
    float m_a = 0.f, sum_a = 0.f;
    int nst_a = 0;
    {
        const uint32_t k_off = sb + SM_RING + (16 * w + (lane & 7) + 8 * l_sel) * 128 + (((lane >> 4) ^ (lane & 7)) << 4);
        uint32_t rem_sc, rem_bar;
        asm("mapa.shared::cluster.u32 %0, %1, %2;" : "=r"(rem_sc) : "r"(sb + SM_SCR), "r"(half ^ 1));
        asm("mapa.shared::cluster.u32 %0, %1, %2;" : "=r"(rem_bar) : "r"(bar_sc), "r"(half ^ 1));
        const uint32_t s_off = (16 * w + 8 * (t & 1) + g) * 4;
        float u[3][4];
#pragma unroll
        for (int j = 0; j < 4; j++) {
#pragma unroll 1
            for (int kt = (j ? 8 * j + KLAG : 0); kt < (j < 3 ? 8 * j + 8 + KLAG : 32); kt++) {
                mbar_wait(bar_full + 8 * slot, ph);
                if (tid == 0) THIST(8);
                const uint32_t base = k_off + slot * TILE;
                uint32_t a[4][4];
#pragma unroll
                for (int ks = 0; ks < 4; ks++) ldsm4(a[ks], base ^ (ks << 5));
                float d0[4], d1[4];
                mma16816z(d0, a[0], qf[0], qf[1]); mma16816z(d1, a[1], qf[2], qf[3]);
                mma16816(d0, a[2], qf[4], qf[5]); mma16816(d1, a[3], qf[6], qf[7]);
                if (lane == 0) mbar_arrive(bar_empty + 8 * slot);
                const float v = (t & 1) ? d0[2] + d1[2] : d0[0] + d1[0];
                if (t < 2) sts32f(sb + SM_SCO + kt * 512 + s_off, v);
                else asm volatile("st.async.weak.shared::cluster.mbarrier::complete_tx::bytes.f32 [%0], %1, [%2];"
                                  :: "r"(rem_sc + kt * 512 + s_off), "f"(v), "r"(rem_bar + (kt >> 3) * 8) : "memory");
                if (++slot == NS) { slot = 0; ph ^= 1; }
            }
            if (j < 3) {
                bar_sync<1, 256>();
                mbar_wait_cluster(bar_sc + 8 * j, 0);
                const float4 p = lds128f(lst + tid * 16 + j * 4096), v = lds128f(lst + tid * 16 + j * 4096 + 16384);
                u[j][0] = score_round(p.x + v.x); u[j][1] = score_round(p.y + v.y);
                u[j][2] = score_round(p.z + v.z); u[j][3] = score_round(p.w + v.w);
            }
            if (j == 2) {
                float mx = -3.0e38f;
#pragma unroll
                for (int i = 0; i < 3; i++) mx = fmaxf(fmaxf(mx, fmaxf(u[i][0], u[i][1])), fmaxf(u[i][2], u[i][3]));
                mx = warp_max(mx);
                if (lane == 0) sts32f(sb + SM_SMAX + w * 4, mx);
                bar_sync<1, 256>();
                {
                    const float4 p = lds128f(sb + SM_SMAX), v = lds128f(sb + SM_SMAX + 16);
                    m_a = fmaxf(fmaxf(fmaxf(p.x, p.y), fmaxf(p.z, p.w)), fmaxf(fmaxf(v.x, v.y), fmaxf(v.z, v.w)));
                }
                uint32_t keep = 0, cnt = 0;
#pragma unroll
                for (int i = 0; i < 3; i++)
#pragma unroll
                    for (int e = 0; e < 4; e++) {
                        const float dlt = u[i][e] - m_a;
                        if (!(dlt < ZERO_P)) { keep |= 1u << (4 * i + e); cnt += 1u << (8 * i); }
                        u[i][e] = ex2_sub(dlt * LOG2E);
                        sum_a += u[i][e];
                    }
                uint32_t inc = cnt;
#pragma unroll
                for (int o = 1; o < 32; o <<= 1) {
                    const uint32_t v = __shfl_up_sync(0xffffffffu, inc, o);
                    if (lane >= o) inc += v;
                }
                if (lane == 31) sts32(sb + SM_SCNT + w * 4, inc);
                bar_sync<1, 256>();
                uint32_t lo = 0, hi = 0, tlo = 0, thi = 0;
                {
                    uint32_t c[8];
                    lds128(c, sb + SM_SCNT); lds128(c + 4, sb + SM_SCNT + 16);
#pragma unroll
                    for (int i = 0; i < 8; i++) {
                        const uint32_t cl = c[i] & 0x00ff00ffu, ch = (c[i] >> 8) & 0xffu;
                        tlo += cl; thi += ch;
                        if (i < w) { lo += cl; hi += ch; }
                    }
                }
                const uint32_t exc = inc - cnt;
                const uint32_t n0 = tlo & 0xffffu, n_a = n0 + thi + (tlo >> 16);
#pragma unroll
                for (int i = 0; i < 3; i++) {
                    const uint32_t pos = i == 0 ? (lo & 0xffffu) : i == 1 ? n0 + hi : n0 + thi + (lo >> 16);
                    uint32_t a = lst + 4 * (pos + ((exc >> (8 * i)) & 0xffu));
#pragma unroll
                    for (int e = 0; e < 4; e++)
                        if (keep & (1u << (4 * i + e))) { sts32f(a, u[i][e]); sts32(a + 16384, (uint32_t)(1024 * i + 4 * tid + e) * 256u); a += 4; }
                }
                nst_a = (int)(n_a + 15) >> 4;
                if (tid < 16 && n_a + tid < 16u * nst_a) { sts32(lst + 4 * (n_a + tid), 0u); sts32(lst + 16384 + 4 * (n_a + tid), (WIN - 1) * 256u); }
            }
        }
    }
    if (tid == 0) TSTAMP(4);

    float o[4][4];
#pragma unroll
    for (int j = 0; j < 4; j++) { o[j][0] = o[j][1] = o[j][2] = o[j][3] = 0.f; }
    uint32_t wo_a[4][4][4];
    const int bb = lane >> 4;
    const u64* msrc = g_ll_m + (bb * 6 + 3) * 256 + 32 * w + 2 * (lane & 15);
    uint4 mc, ms;
    {
        const int dtot = max(1, min(min(8 * (VD - SPARE), nst_a), (nst_a * (4 * VDEPTH / 3) + 128) >> 8));
        const int dd = (dtot + 7 - w) >> 3;
        const int wrap = dtot - 8 * (dd - 1);
        u64 pol;
        asm volatile("createpolicy.fractional.L2::evict_first.b64 %0, 1.0;" : "=l"(pol));
        const char* vsrc[4];
        {
            const char* vb = reinterpret_cast<const char*>(vcache) + ((size_t)(r >> 1) * SK + (SK - WIN)) * 256 + half * 128;
            const uint32_t x0 = ((lane & 7) ^ ((lane >> 1) & 4)) << 4;
#pragma unroll
            for (int j = 0; j < 4; j++) { vsrc[j] = vb + (x0 ^ (j << 4)); asm volatile("" : "+l"(vsrc[j])); }
        }
        const uint32_t ring = sb + SM_RING + w * (VD * 2048);
        uint32_t vdst = ring + (lane >> 3) * 512 + (lane & 7) * 16, lrow = lst + (lane >> 3) * 16;
        asm volatile("" : "+r"(vdst), "+r"(lrow));
        int ik = 0, ist = w, id = 0, isl = 0;
        float sc_a = 1.0f, sc_b = 1.0f;
        const char* nsrc[4];
        float npr[4];
        auto prep = [&]() {
            uint32_t en[4];
            lds128(en, lrow + 16384 + ist * 64);
            const float4 ev = lds128f(lrow + ist * 64);
            const float f = ist < nst_a ? sc_a : sc_b;
            npr[0] = ev.x * f; npr[1] = ev.y * f; npr[2] = ev.z * f; npr[3] = ev.w * f;
#pragma unroll
            for (int j = 0; j < 4; j++) nsrc[j] = vsrc[j] + en[j];
        };
        auto fire = [&]() {
#pragma unroll
            for (int j = 0; j < 4; j++)
                asm volatile("cp.async.cg.shared.global.L2::cache_hint [%0], [%1], 16, %2, %3;"
                             :: "r"(vdst + isl * 2048 + j * 128), "l"(nsrc[j]), "r"(npr[j] <= 0x1p-134f ? 0 : 16), "l"(pol) : "memory");
            asm volatile("cp.async.commit_group;" ::: "memory");
            ik++;
            if (++id == dd) { id = 0; ist += wrap; } else ist += 8;
            if (++isl == VD) isl = 0;
        };
        bar_sync<1, 256>();
#pragma unroll 1
        while (ik < dd) { prep(); fire(); }
        if (tid == 0) TSTAMP(20);
        int nst;
        {
            mbar_wait_cluster(bar_sc + 24, 0);
            if (tid == 0) TSTAMP(21);
            const float4 p = lds128f(lst + tid * 16 + 12288), v = lds128f(lst + tid * 16 + 12288 + 16384);
            float u[4] = {score_round(p.x + v.x), score_round(p.y + v.y), score_round(p.z + v.z), score_round(p.w + v.w)};
            float mx = warp_max(fmaxf(fmaxf(u[0], u[1]), fmaxf(u[2], u[3])));
            if (lane == 0) sts32f(sb + SM_SMAX + w * 4, mx);
            bar_sync<1, 256>();
            {
                const float4 p2 = lds128f(sb + SM_SMAX), v2 = lds128f(sb + SM_SMAX + 16);
                mx = fmaxf(m_a, fmaxf(fmaxf(fmaxf(p2.x, p2.y), fmaxf(p2.z, p2.w)), fmaxf(fmaxf(v2.x, v2.y), fmaxf(v2.z, v2.w))));
            }
            if (tid == 0) TSTAMPD(22, __float_as_uint(mx));
            const float ca = ex2_sub((m_a - mx) * LOG2E);
            float sum = sum_a * ca;
            uint32_t keep = 0, cnt = 0;
#pragma unroll
            for (int e = 0; e < 4; e++) {
                const float dlt = u[e] - mx;
                if (!(dlt < ZERO_P)) { keep |= 1u << e; cnt++; }
                u[e] = ex2_sub(dlt * LOG2E);
                sum += u[e];
            }
            uint32_t inc = cnt;
#pragma unroll
            for (int of = 1; of < 32; of <<= 1) {
                const uint32_t vv = __shfl_up_sync(0xffffffffu, inc, of);
                if (lane >= of) inc += vv;
                sum += __shfl_xor_sync(0xffffffffu, sum, of);
            }
            if (lane == 31) { sts32f(sb + SM_SSUM + w * 4, sum); sts32(sb + SM_SCNT + w * 4, inc); }
            bar_sync<1, 256>();
            {
                const float4 p2 = lds128f(sb + SM_SSUM), v2 = lds128f(sb + SM_SSUM + 16);
                sum = ((p2.x + p2.y) + (p2.z + p2.w)) + ((v2.x + v2.y) + (v2.z + v2.w));
            }
            if (tid == 0) TSTAMPD(28, __float_as_uint(sum));
            uint32_t pos = 16 * nst_a, n = pos;
            {
                uint32_t c[8];
                lds128(c, sb + SM_SCNT); lds128(c + 4, sb + SM_SCNT + 16);
#pragma unroll
                for (int i = 0; i < 8; i++) { n += c[i]; if (i < w) pos += c[i]; }
            }
            uint32_t a = lst + 4 * (pos + inc - cnt);
#pragma unroll
            for (int e = 0; e < 4; e++)
                if (keep & (1u << e)) { sts32f(a, u[e]); sts32(a + 16384, (uint32_t)(3072 + 4 * tid + e) * 256u); a += 4; }
            nst = (int)(n + 15) >> 4;
            if (tid < 16 && n + tid < 16u * nst) { sts32(lst + 4 * (n + tid), 0u); sts32(lst + 16384 + 4 * (n + tid), (WIN - 1) * 256u); }
            sc_b = rcp_fast(sum);
            sc_a = ca * sc_b;
            bar_sync<1, 256>();
        }
        if (tid == 0) TSTAMP(5);
        const int rounds = nst / dtot;
        const int nw = rounds * dd + max(0, (nst - rounds * dtot + 7 - w) >> 3);
        {
            uint32_t* dst = g_ll_r + ((b * 16 + 2 * w) * NPP + cg) * 32 + t * 8 + g;
            tag_st(dst, 0.f, (flag & 3u) ^ 2u); tag_st(dst + NPP * 32, 0.f, (flag & 3u) ^ 2u);
        }
        bool polled = false;
        int ck = 0, cst = w, cd = 0, csl = 0;
#pragma unroll 1
        do {
            if (!polled && ik + POLL_REM >= nw) {
                polled = true;
                bar_arrive<4, 288>();
                if (is_ffn) { ll_ld2(msrc, ms); ll_ld2(msrc + 256, mc); }
            }
            if (ck < nw) {
                const bool more = ik < nw && ik - ck <= dd;
                if (more) prep();
                const float2 e0 = lds64f(lst + cst * 64 + t * 8), e1 = lds64f(lst + cst * 64 + 32 + t * 8);
                const float sc = cst < nst_a ? sc_a : sc_b;
                const uint32_t b0 = pack_bf16(e0.x * sc, e0.y * sc), b1 = pack_bf16(e1.x * sc, e1.y * sc);
                switch (ik - ck) {
                    case 1: asm volatile("cp.async.wait_group 0;" ::: "memory"); break;
                    case 2: asm volatile("cp.async.wait_group 1;" ::: "memory"); break;
                    case 3: asm volatile("cp.async.wait_group 2;" ::: "memory"); break;
                    case 4: asm volatile("cp.async.wait_group 3;" ::: "memory"); break;
                    case 5: asm volatile("cp.async.wait_group 4;" ::: "memory"); break;
                    case 6: asm volatile("cp.async.wait_group 5;" ::: "memory"); break;
                    default: asm volatile("cp.async.wait_group 6;" ::: "memory"); break;
                }
                __syncwarp();
                if (more) fire();
                if (lane == 0) THIST(1);
                const uint32_t base = ring + csl * 2048 + tr_off;
                uint32_t a[4][4];
#pragma unroll
                for (int j = 0; j < 4; j++) ldsm4t(a[j], base ^ (j << 5));
#pragma unroll
                for (int j = 0; j < 4; j++) mma16816(o[j], a[j], b0, b1);
                if (++cd == dd) { cd = 0; cst += wrap; } else cst += 8;
                if (++csl == VD) csl = 0;
            }
            if (ck == 0) {
                mbar_wait(bar_w + 8 * (w >> 1), 1);
#pragma unroll
                for (int j = 0; j < 4; j++)
#pragma unroll
                    for (int ks = 0; ks < 4; ks++) ldsm4t(wo_a[ks][j], ((sb + SM_W + w * 8192 + tr_off) ^ (j << 5)) + ks * 2048);
                __syncwarp();
                if (lane == 0) mbar_arrive(bar_wfree);
            }
        } while (++ck < nw);
    }
    TSTAMPD(6, __float_as_uint(o[3][0]));

    const uint32_t tag = flag & 3u;
    {
        sts32f(sb + SM_RO + red_st, sel4(t, o[0][0], o[1][0], o[2][0], o[3][0]));
        sts32f(sb + SM_RO + red_st + 32, sel4(t, o[0][2], o[1][2], o[2][2], o[3][2]));
        uint32_t* dst = g_ll_r + ((b * 16 + 2 * w) * NPP + cg) * 32 + t * 8 + g;
        bar_sync<1, 256>();
        float2 v[8];
#pragma unroll
        for (int i = 0; i < 8; i++) v[i] = lds64f(sb + SM_RO + i * 256 + lane * 8);
        const float o0 = ((v[0].x + v[1].x) + (v[2].x + v[3].x)) + ((v[4].x + v[5].x) + (v[6].x + v[7].x));
        const float o1 = ((v[0].y + v[1].y) + (v[2].y + v[3].y)) + ((v[4].y + v[5].y) + (v[6].y + v[7].y));
        const uint32_t op = pack_bf16(o0, o1);
        uint32_t bf[8];
#pragma unroll
        for (int i = 0; i < 8; i++) bf[i] = __shfl_sync(0xffffffffu, op, 4 * i + t);
        float d[2][4][4];
#pragma unroll
        for (int ks = 0; ks < 4; ks++)
#pragma unroll
            for (int j = 0; j < 4; j++) {
                if (ks < 2) mma16816z(d[ks][j], wo_a[ks][j], bf[2 * ks], bf[2 * ks + 1]);
                else        mma16816(d[ks & 1][j], wo_a[ks][j], bf[2 * ks], bf[2 * ks + 1]);
            }
        const float r0 = sel4(t, d[0][0][0], d[0][0][2], d[0][1][0], d[0][1][2]) + sel4(t, d[1][0][0], d[1][0][2], d[1][1][0], d[1][1][2]);
        const float r1 = sel4(t, d[0][2][0], d[0][2][2], d[0][3][0], d[0][3][2]) + sel4(t, d[1][2][0], d[1][2][2], d[1][3][0], d[1][3][2]);
        tag_st(dst, r0, tag);
        tag_st(dst + NPP * 32, r1, tag);
        TSTAMPD(23, op);
        TSTAMPD(7, __float_as_uint(r1));
    }
    auto gather = [&](int box, int per, int n) {
        const uint32_t* src = g_ll_r + (box * NPP + per * w) * 32 + lane;
        float s0, s1;
        while (true) {
            uint32_t v[11], bad = 0;
#pragma unroll
            for (int i = 0; i < 11; i++) {
                v[i] = tag;
                if (i < 8 || i < n) asm volatile("ld.relaxed.gpu.global.u32 %0, [%1];" : "=r"(v[i]) : "l"(src + i * 32) : "memory");
            }
#pragma unroll
            for (int i = 0; i < 11; i++) {
                v[i] ^= tag; bad |= v[i];
                if (i == 0) s0 = __uint_as_float(v[i]); else if (i == 1) s1 = __uint_as_float(v[i]);
                else if (i & 1) s1 += __uint_as_float(v[i]); else s0 += __uint_as_float(v[i]);
            }
            if (__all_sync(0xffffffffu, (bad & 3u) == 0)) break;
            check_timeout(t0);
        }
        sts32f(sb + SM_RQ + w * 128 + lane * 4, s0 + s1);
        TSTAMPD(r < 32 ? 26 : 27, __float_as_uint(s0));
        bar_arrive<6, 288>();
    };
#define DUMPH() do { } while (0)
    if (!is_ffn) {
        if (r >= 96) gather(r - 96, 8, 8);
        DUMPH();
        return;
    }

    uint32_t f_a[2][4][4], w2_a[4][4];
    {
        mbar_wait(bar_f, 0);
        const uint32_t fb = sb + SM_W + l_sel * 16384 + (64 * w + l_row) * 32 + ((g & 1) << 4);
#pragma unroll
        for (int j = 0; j < 2; j++)
#pragma unroll
            for (int ks = 0; ks < 4; ks++) ldsm4t(f_a[j][ks], (fb ^ (j << 4)) + ks * 512);
        mbar_wait(bar_f2, 0);
#pragma unroll
        for (int j = 0; j < 4; j++) ldsm4t(w2_a[j], (sb + SM_W + 32768 + w * 2048 + tr_off) ^ (j << 5));
    }
    {
        while (!__all_sync(0xffffffffu, ms.y == flag && ms.w == flag && mc.y == flag && mc.w == flag)) {
            ll_ld2(msrc, ms); ll_ld2(msrc + 256, mc); check_timeout(t0);
        }
        uint32_t* dst = g_ll_r + ((32 + 4 * w) * NPP + r) * 32 + t * 8 + g;
#pragma unroll
        for (int j = 0; j < 4; j++) tag_st(dst + j * NPP * 32, 0.f, tag ^ 2u);
        uint4 xv;
        xv.y = ~flag;
        ll_poll2(g_ll_x + bb * 256 + 32 * w + 2 * (lane & 15), xv, flag, t0);
        TSTAMPD(9, xv.x);
        if (r < 32) bar_arrive<7, 288>();
        const float piv = bf_lo(__shfl_sync(0xffffffffu, xv.x, lane & 16));
        const float e0 = bf_lo(xv.x) - piv, e1 = bf_hi(xv.x) - piv, e2 = bf_lo(xv.z) - piv, e3 = bf_hi(xv.z) - piv;
        float s1 = (e0 + e1) + (e2 + e3), s2 = (e0 * e0 + e1 * e1) + (e2 * e2 + e3 * e3);
#pragma unroll
        for (int of = 1; of < 16; of <<= 1) { s1 += __shfl_xor_sync(0xffffffffu, s1, of); s2 += __shfl_xor_sync(0xffffffffu, s2, of); }
        if ((lane & 15) == 0) sts64f(sb + SM_STAT + bb * 64 + w * 8, piv + s1 * (1.0f / 64.0f), s2 - s1 * s1 * (1.0f / 64.0f));
        bar_sync<1, 256>();
        float4 st[4];
#pragma unroll
        for (int i = 0; i < 4; i++) st[i] = lds128f(sb + SM_STAT + bb * 64 + i * 16);
        const float mean = (((st[0].x + st[0].z) + (st[1].x + st[1].z)) + ((st[2].x + st[2].z) + (st[3].x + st[3].z))) * 0.125f;
        const float M2 = ((st[0].y + st[0].w) + (st[1].y + st[1].w)) + ((st[2].y + st[2].w) + (st[3].y + st[3].w));
        float dv[4];
#pragma unroll
        for (int i = 0; i < 4; i++) { const float d0 = st[i].x - mean, d1 = st[i].z - mean; dv[i] = d0 * d0 + d1 * d1; }
        const float rden = ln_rden(fmaxf(M2 * (1.0f / DM) + ((dv[0] + dv[1]) + (dv[2] + dv[3])) * 0.125f, 0.f));
        TSTAMPD(24, __float_as_uint(st[3].x));
        const uint32_t m2 = pack_bf16(mean, mean);
        const uint32_t p0 = bf2_add(bf2_mul(ln_pair(xv.x, m2, rden), mc.x), ms.x);
        const uint32_t p1 = bf2_add(bf2_mul(ln_pair(xv.z, m2, rden), mc.z), ms.z);
        TSTAMPD(25, p1);
        float d[2][4][4];
#pragma unroll
        for (int ks = 0; ks < 4; ks++) {
            const uint32_t b0 = __shfl_sync(0xffffffffu, p0, 16 * (g & 1) + 4 * ks + t);
            const uint32_t b1 = __shfl_sync(0xffffffffu, p1, 16 * (g & 1) + 4 * ks + t);
#pragma unroll
            for (int j = 0; j < 2; j++) mma16816z(d[j][ks], f_a[j][ks], b0, b1);
        }
        float acc[4];
#pragma unroll
        for (int i = 0; i < 4; i++) {
            const float u0 = (d[0][0][i] + d[0][1][i]) + (d[0][2][i] + d[0][3][i]);
            const float u1 = (d[1][0][i] + d[1][1][i]) + (d[1][2][i] + d[1][3][i]);
            acc[i] = (t & 1) ? u1 : u0;
        }
        if (t < 2) sts128f(sb + SM_RGU + w * 256 + (8 * t + g) * 16, acc[0], acc[2], acc[1], acc[3]);
        bar_sync<1, 256>();
        float2 pv[8];
#pragma unroll
        for (int i = 0; i < 8; i++) pv[i] = lds64f(sb + SM_RGU + i * 256 + (lane & 15) * 16 + bb * 8);
        const float gate = bf16r(((pv[0].x + pv[1].x) + (pv[2].x + pv[3].x)) + ((pv[4].x + pv[5].x) + (pv[6].x + pv[7].x)));
        const float up   = bf16r(((pv[0].y + pv[1].y) + (pv[2].y + pv[3].y)) + ((pv[4].y + pv[5].y) + (pv[6].y + pv[7].y)));
        TSTAMPD(10, __float_as_uint(pv[7].x));
        const float hh = bf16r(silu_f(gate)) * up;
        const int sl0 = 16 * (g & 1) + 2 * t;
        const float h0 = __shfl_sync(0xffffffffu, hh, sl0), h1 = __shfl_sync(0xffffffffu, hh, sl0 + 1);
        const float h8 = __shfl_sync(0xffffffffu, hh, sl0 + 8), h9 = __shfl_sync(0xffffffffu, hh, sl0 + 9);
        const uint32_t b0 = pack_bf16(h0, h1), b1 = pack_bf16(h8, h9);
        float f[4][4];
#pragma unroll
        for (int j = 0; j < 4; j++) mma16816z(f[j], w2_a[j], b0, b1);
#pragma unroll
        for (int j = 0; j < 4; j++) tag_st(dst + j * NPP * 32, sel4(t, f[j][0], f[j][1], f[j][2], f[j][3]), tag);
        TSTAMPD(11, __float_as_uint(f[3][3]));
        if (r < 32) {
            { const uint32_t c = clk32(); while (clk32() - c < XDELAY) ; }
            gather(32 + r, 11, w < 7 ? 11 : NFFN - 77);
        }
        DUMPH();
    }
}

typedef CUresult (*EncodeFn)(CUtensorMap*, CUtensorMapDataType, cuuint32_t, void*, const cuuint64_t*, const cuuint64_t*,
                             const cuuint32_t*, const cuuint32_t*, CUtensorMapInterleave, CUtensorMapSwizzle,
                             CUtensorMapL2promotion, CUtensorMapFloatOOBfill);

void make_map(EncodeFn enc, CUtensorMap* tm, const void* ptr, uint64_t cols, uint64_t rows, uint32_t box_cols,
              uint32_t box_rows, CUtensorMapSwizzle sw, CUtensorMapL2promotion promo) {
    cuuint64_t gd[2] = {cols, rows};
    cuuint64_t gs[1] = {cols * 2};
    cuuint32_t box[2] = {box_cols, box_rows};
    cuuint32_t es[2] = {1, 1};
    enc(tm, CU_TENSOR_MAP_DATA_TYPE_BFLOAT16, 2, const_cast<void*>(ptr), gd, gs, box, es, CU_TENSOR_MAP_INTERLEAVE_NONE,
        sw, promo, CU_TENSOR_MAP_FLOAT_OOB_FILL_NONE);
}

}

extern "C" void kernel_launch(void* const* d_in, const int* in_sizes, int n_in, void* d_out, int out_size) {
    (void)in_sizes; (void)n_in; (void)out_size;
    static EncodeFn enc = nullptr;
    if (!enc) {
        cudaDriverEntryPointQueryResult qr;
        cudaGetDriverEntryPoint("cuTensorMapEncodeTiled", (void**)&enc, cudaEnableDefault, &qr);
        cudaFuncSetAttribute(fused_decode_kernel, cudaFuncAttributeMaxDynamicSharedMemorySize, SMEM_BYTES);
    }
    Maps tm;
    const CUtensorMapSwizzle S128 = CU_TENSOR_MAP_SWIZZLE_128B;
    const CUtensorMapL2promotion P256 = CU_TENSOR_MAP_L2_PROMOTION_L2_256B, P128 = CU_TENSOR_MAP_L2_PROMOTION_L2_128B;
    make_map(enc, &tm.K, d_in[1], 128, (uint64_t)64 * SK, 64, 128, S128, P128);
    make_map(enc, &tm.V, d_in[2], 128, (uint64_t)64 * SK, 64, 128, S128, P128);
    make_map(enc, &tm.Wq, d_in[3], 4096, 512, 64, 128, S128, P256);
    make_map(enc, &tm.Wo, d_in[4], 512, 4096, 64, 64, S128, P256);
    make_map(enc, &tm.W2, d_in[8], 512, FF, 64, 16, S128, P256);
    make_map(enc, &tm.Wm, d_in[10], 6 * DM, 512, 8, 256, CU_TENSOR_MAP_SWIZZLE_NONE, P128);
    make_map(enc, &tm.Wm16, d_in[10], 6 * DM, 512, 16, 256, CU_TENSOR_MAP_SWIZZLE_32B, P128);
    make_map(enc, &tm.W1, d_in[6], FF, 512, 16, 256, CU_TENSOR_MAP_SWIZZLE_32B, P128);
    make_map(enc, &tm.W3, d_in[7], FF, 512, 16, 256, CU_TENSOR_MAP_SWIZZLE_32B, P128);
    fused_decode_kernel<<<NCTA, NTHREADS, SMEM_BYTES>>>(
        (const bf16*)d_in[0], (const bf16*)d_in[9], (const bf16*)d_in[2], (const bf16*)d_in[10], (const bf16*)d_in[6],
        (const bf16*)d_in[7], (const bf16*)d_in[8], (bf16*)d_out, tm);
}
```

```cpp
#include <cuda_runtime.h>
#include <cuda.h>
#include <cuda_bf16.h>
#include <stdint.h>

namespace {

typedef __nv_bfloat16 bf16;
typedef unsigned long long u64;

constexpr int DM   = 512;
constexpr int SK   = 16384;
constexpr int WIN  = 4096;
constexpr int FF   = 1376;
constexpr int NCTA = 128;
constexpr int NFFN = 86;
constexpr int NPP  = 88;
constexpr int NS   = 7;
constexpr int TILE = 16384;
#define BURST 5
#define NPF 3
#define FSTEADY 4
#define RELD 5
#define HDELAY 2400u
#define XDELAY 300u
#define VD 7
#define VDEPTH 42
#define KLAG 2
#define POLL_REM 4
#define TH_MUL 0
#define THETA 1
constexpr int NTHREADS = 320;

constexpr int SM_W    = 0;
constexpr int SM_RING = 65536;
constexpr int SM_SCO  = SM_RING + NS * TILE;
constexpr int SM_SCR  = SM_SCO + 16384;
constexpr int SM_P    = SM_SCR + 16384;
constexpr int SM_RMOD = SM_P + 8192;
constexpr int SM_RQ   = SM_RMOD + 512;
constexpr int SM_RO   = SM_RQ + 2048;
constexpr int SM_RGU  = SM_RO + 2048;
constexpr int SM_SILU = SM_RGU + 2048;
constexpr int SM_STAT = SM_SILU + 2048;
constexpr int SM_SMAX = SM_STAT + 128;
constexpr int SM_SSUM = SM_SMAX + 32;
constexpr int SM_SCNT = SM_SSUM + 32;
constexpr int SM_BAR  = SM_SCNT + 32;
constexpr int SM_HIST = SM_BAR + 8 * (2 * NS + 14);
constexpr int SM_END  = SM_HIST;
static_assert(VD * 2048 * 8 <= NS * TILE, "V rings");
constexpr int SMEM_BYTES = SM_END + 1024;
static_assert(SMEM_BYTES <= 232448, "smem");

__device__ unsigned int g_epoch;
__device__ __align__(128) u64 g_ll_x[2 * 256];
__device__ __align__(128) u64 g_ll_m[2 * 6 * 256];
__device__ __align__(128) uint32_t g_ll_r[2 * 32 * NPP * 32];
#define THIST(wgt) do { } while (0)
#define TSTAMP(i) do { } while (0)
#define TSTAMPD(i, dep) do { } while (0)

__device__ __forceinline__ uint32_t smem_u32(const void* p) { return (uint32_t)__cvta_generic_to_shared(p); }
__device__ __forceinline__ uint32_t pack_bf16(float lo, float hi) {
    uint32_t r; asm("cvt.rn.bf16x2.f32 %0, %1, %2;" : "=r"(r) : "f"(hi), "f"(lo)); return r;
}
__device__ __forceinline__ float bf16r(float v) { return __uint_as_float(pack_bf16(0.0f, v)); }
__device__ __forceinline__ float bf_lo(uint32_t v) { return __uint_as_float(v << 16); }
__device__ __forceinline__ float bf_hi(uint32_t v) { return __uint_as_float(v & 0xffff0000u); }
__device__ __forceinline__ uint32_t bf2_mul(uint32_t a, uint32_t b) { uint32_t r; asm("mul.rn.bf16x2 %0, %1, %2;" : "=r"(r) : "r"(a), "r"(b)); return r; }
__device__ __forceinline__ uint32_t bf2_add(uint32_t a, uint32_t b) { uint32_t r; asm("add.rn.bf16x2 %0, %1, %2;" : "=r"(r) : "r"(a), "r"(b)); return r; }
__device__ __forceinline__ uint32_t bf2_sub(uint32_t a, uint32_t b) { uint32_t r; asm("sub.rn.bf16x2 %0, %1, %2;" : "=r"(r) : "r"(a), "r"(b)); return r; }
__device__ __forceinline__ float ex2_fast(float v) { float r; asm("ex2.approx.ftz.f32 %0, %1;" : "=f"(r) : "f"(v)); return r; }
__device__ __forceinline__ float ex2_sub(float v) { float r; asm("ex2.approx.f32 %0, %1;" : "=f"(r) : "f"(v)); return r; }
__device__ __forceinline__ float sqrt_fast(float v) { float r; asm("sqrt.approx.ftz.f32 %0, %1;" : "=f"(r) : "f"(v)); return r; }
__device__ __forceinline__ float rcp_fast(float v) { float r; asm("rcp.approx.ftz.f32 %0, %1;" : "=f"(r) : "f"(v)); return r; }
constexpr float LOG2E = 1.4426950408889634f;
__device__ __forceinline__ float silu_f(float v) { return v * rcp_fast(1.0f + ex2_fast(-LOG2E * v)); }
__device__ __forceinline__ float score_round(float v) { return bf16r(bf16r(v) * 0.08838834764831845f); }
__device__ __forceinline__ float warp_max(float v) {
    int i = __float_as_int(v);
    i ^= (i >> 31) & 0x7fffffff;
    i = __reduce_max_sync(0xffffffffu, i);
    i ^= (i >> 31) & 0x7fffffff;
    return __int_as_float(i);
}
__device__ __forceinline__ float ln_rden(float var) { return rcp_fast(bf16r(sqrt_fast(bf16r(bf16r(var) + 1e-5f)))); }
__device__ __forceinline__ uint32_t ln_pair(uint32_t x2, uint32_t m2, float rden) {
    const uint32_t d = bf2_sub(x2, m2);
    return pack_bf16(bf_lo(d) * rden, bf_hi(d) * rden);
}

__device__ __forceinline__ void mbar_init(uint32_t bar, uint32_t cnt) {
    asm volatile("mbarrier.init.shared::cta.b64 [%0], %1;" :: "r"(bar), "r"(cnt) : "memory");
}
__device__ __forceinline__ void mbar_expect_tx(uint32_t bar, uint32_t bytes) {
    asm volatile("mbarrier.arrive.expect_tx.shared::cta.b64 _, [%0], %1;" :: "r"(bar), "r"(bytes) : "memory");
}
__device__ __forceinline__ void mbar_arrive(uint32_t bar) {
    asm volatile("mbarrier.arrive.shared::cta.b64 _, [%0];" :: "r"(bar) : "memory");
}
__device__ __forceinline__ uint32_t clk32() { uint32_t c; asm volatile("mov.u32 %0, %%clock;" : "=r"(c)); return c; }
__device__ __forceinline__ void check_timeout(uint32_t t0) { if ((int32_t)(clk32() - t0) < 0) __trap(); }
#define MBAR_WAIT_ASM(SEM) \
    asm volatile("{\n.reg .pred p;\n.reg .s32 t1;\n" \
                 "W_%=:\n" \
                 "mbarrier.try_wait.parity" SEM ".shared::cta.b64 p, [%0], %1;\n@p bra D_%=;\n" \
                 "mov.u32 t1, %%clock;\nsub.s32 t1, t1, %2;\nsetp.ge.s32 p, t1, 0;\n@p bra W_%=;\ntrap;\n" \
                 "D_%=:\n}" :: "r"(bar), "r"(parity), "r"(t0) : "memory")
__device__ __forceinline__ void mbar_wait_t(uint32_t bar, uint32_t parity, uint32_t t0) { MBAR_WAIT_ASM(""); }
__device__ __forceinline__ void mbar_wait_cluster_t(uint32_t bar, uint32_t parity, uint32_t t0) { MBAR_WAIT_ASM(".acquire.cluster"); }
#define mbar_wait(bar, parity) mbar_wait_t(bar, parity, t0)
#define mbar_wait_cluster(bar, parity) mbar_wait_cluster_t(bar, parity, t0)
__device__ __forceinline__ bool mbar_test(uint32_t bar, uint32_t parity) {
    uint32_t ok;
    asm volatile("{\n.reg .pred p;\nmbarrier.test_wait.parity.shared::cta.b64 p, [%1], %2;\nselp.u32 %0, 1, 0, p;\n}"
                 : "=r"(ok) : "r"(bar), "r"(parity) : "memory");
    return ok != 0;
}
__device__ __forceinline__ bool elect_one() {
    uint32_t p;
    asm volatile("{\n.reg .pred P;\nelect.sync _|P, 0xffffffff;\nselp.u32 %0, 1, 0, P;\n}" : "=r"(p));
    return p != 0;
}
__device__ __forceinline__ void tma2d(uint32_t dst, const CUtensorMap* tm, int c0, int c1, uint32_t bar) {
    asm volatile("cp.async.bulk.tensor.2d.shared::cluster.global.mbarrier::complete_tx::bytes [%0], [%1, {%3, %4}], [%2];"
                 :: "r"(dst), "l"(tm), "r"(bar), "r"(c0), "r"(c1) : "memory");
}
__device__ __forceinline__ void tma2d_ef(uint32_t dst, const CUtensorMap* tm, int c0, int c1, uint32_t bar, u64 pol) {
    asm volatile("cp.async.bulk.tensor.2d.shared::cluster.global.mbarrier::complete_tx::bytes.L2::cache_hint [%0], [%1, {%3, %4}], [%2], %5;"
                 :: "r"(dst), "l"(tm), "r"(bar), "r"(c0), "r"(c1), "l"(pol) : "memory");
}
__device__ __forceinline__ void ldsm2t(uint32_t& a0, uint32_t& a1, uint32_t addr) {
    asm volatile("ldmatrix.sync.aligned.m8n8.x2.trans.shared.b16 {%0,%1}, [%2];" : "=r"(a0), "=r"(a1) : "r"(addr) : "memory");
}
__device__ __forceinline__ void ldsm4(uint32_t (&a)[4], uint32_t addr) {
    asm volatile("ldmatrix.sync.aligned.m8n8.x4.shared.b16 {%0,%1,%2,%3}, [%4];"
                 : "=r"(a[0]), "=r"(a[1]), "=r"(a[2]), "=r"(a[3]) : "r"(addr) : "memory");
}
__device__ __forceinline__ void ldsm4t(uint32_t (&a)[4], uint32_t addr) {
    asm volatile("ldmatrix.sync.aligned.m8n8.x4.trans.shared.b16 {%0,%1,%2,%3}, [%4];"
                 : "=r"(a[0]), "=r"(a[1]), "=r"(a[2]), "=r"(a[3]) : "r"(addr) : "memory");
}
__device__ __forceinline__ void mma16816(float (&d)[4], const uint32_t (&a)[4], uint32_t b0, uint32_t b1) {
    asm volatile("mma.sync.aligned.m16n8k16.row.col.f32.bf16.bf16.f32 {%0,%1,%2,%3}, {%4,%5,%6,%7}, {%8,%9}, {%0,%1,%2,%3};"
                 : "+f"(d[0]), "+f"(d[1]), "+f"(d[2]), "+f"(d[3])
                 : "r"(a[0]), "r"(a[1]), "r"(a[2]), "r"(a[3]), "r"(b0), "r"(b1));
}
__device__ __forceinline__ void mma16816z(float (&d)[4], const uint32_t (&a)[4], uint32_t b0, uint32_t b1) {
    asm volatile("mma.sync.aligned.m16n8k16.row.col.f32.bf16.bf16.f32 {%0,%1,%2,%3}, {%4,%5,%6,%7}, {%8,%9}, {%10,%10,%10,%10};"
                 : "=f"(d[0]), "=f"(d[1]), "=f"(d[2]), "=f"(d[3])
                 : "r"(a[0]), "r"(a[1]), "r"(a[2]), "r"(a[3]), "r"(b0), "r"(b1), "f"(0.0f));
}
template <int ID, int N> __device__ __forceinline__ void bar_sync() { asm volatile("bar.sync %0, %1;" :: "n"(ID), "n"(N) : "memory"); }
template <int ID, int N> __device__ __forceinline__ void bar_arrive() { asm volatile("bar.arrive %0, %1;" :: "n"(ID), "n"(N) : "memory"); }
__device__ __forceinline__ void cluster_arrive_relaxed() { asm volatile("barrier.cluster.arrive.relaxed.aligned;" ::: "memory"); }
__device__ __forceinline__ void cluster_wait() { asm volatile("barrier.cluster.wait.acquire.aligned;" ::: "memory"); }

__device__ __forceinline__ void sts32f(uint32_t a, float v) { asm volatile("st.shared.f32 [%0], %1;" :: "r"(a), "f"(v) : "memory"); }
__device__ __forceinline__ void sts32(uint32_t a, uint32_t v) { asm volatile("st.shared.b32 [%0], %1;" :: "r"(a), "r"(v) : "memory"); }
__device__ __forceinline__ uint32_t lds32(uint32_t a) { uint32_t v; asm volatile("ld.shared.b32 %0, [%1];" : "=r"(v) : "r"(a) : "memory"); return v; }
__device__ __forceinline__ float2 lds64f(uint32_t a) { float2 v; asm volatile("ld.shared.v2.f32 {%0,%1}, [%2];" : "=f"(v.x), "=f"(v.y) : "r"(a) : "memory"); return v; }
__device__ __forceinline__ float4 lds128f(uint32_t a) { float4 v; asm volatile("ld.shared.v4.f32 {%0,%1,%2,%3}, [%4];" : "=f"(v.x), "=f"(v.y), "=f"(v.z), "=f"(v.w) : "r"(a) : "memory"); return v; }
__device__ __forceinline__ void lds128(uint32_t* v, uint32_t a) { asm volatile("ld.shared.v4.b32 {%0,%1,%2,%3}, [%4];" : "=r"(v[0]), "=r"(v[1]), "=r"(v[2]), "=r"(v[3]) : "r"(a) : "memory"); }
__device__ __forceinline__ void sts64f(uint32_t a, float x, float y) { asm volatile("st.shared.v2.f32 [%0], {%1,%2};" :: "r"(a), "f"(x), "f"(y) : "memory"); }
__device__ __forceinline__ void sts128(uint32_t a, uint32_t x, uint32_t y, uint32_t z, uint32_t w) { asm volatile("st.shared.v4.b32 [%0], {%1,%2,%3,%4};" :: "r"(a), "r"(x), "r"(y), "r"(z), "r"(w) : "memory"); }
__device__ __forceinline__ void sts128f(uint32_t a, float x, float y, float z, float w) { asm volatile("st.shared.v4.f32 [%0], {%1,%2,%3,%4};" :: "r"(a), "f"(x), "f"(y), "f"(z), "f"(w) : "memory"); }

__device__ __forceinline__ void ll_st(u64* p, uint32_t lo, uint32_t hi) {
    asm volatile("{\n.reg .b64 v;\nmov.b64 v, {%1, %2};\nst.relaxed.gpu.global.b64 [%0], v;\n}" :: "l"(p), "r"(lo), "r"(hi) : "memory");
}
__device__ __forceinline__ void ll_ld2(const u64* p, uint4& v) {
    asm volatile("{\n.reg .b64 a, b;\nld.relaxed.gpu.global.v2.b64 {a, b}, [%4];\nmov.b64 {%0, %1}, a;\nmov.b64 {%2, %3}, b;\n}"
                 : "=r"(v.x), "=r"(v.y), "=r"(v.z), "=r"(v.w) : "l"(p) : "memory");
}
__device__ __forceinline__ void ll_poll2(const u64* p, uint4& v, uint32_t flag, uint32_t t0) {
    while (!__all_sync(0xffffffffu, v.y == flag && v.w == flag)) { ll_ld2(p, v); check_timeout(t0); }
}
__device__ __forceinline__ void tag_st(uint32_t* p, float v, uint32_t tag) {
    asm volatile("st.relaxed.gpu.global.u32 [%0], %1;" :: "l"(p), "r"((__float_as_uint(v) & ~3u) | tag) : "memory");
}
__device__ __forceinline__ float sel4(int t, float a, float b, float c, float d) {
    float lo = (t & 1) ? b : a, hi = (t & 1) ? d : c;
    return (t & 2) ? hi : lo;
}

struct Maps { CUtensorMap K, Wq, Wo, W2, Wm, W1, W3, Wm16; };

__global__ void __cluster_dims__(2, 1, 1) __launch_bounds__(NTHREADS, 1)
fused_decode_kernel(const bf16* __restrict__ x, const bf16* __restrict__ cvec, const bf16* __restrict__ vcache,
                    bf16* __restrict__ out, const __grid_constant__ Maps tm)
{
    extern __shared__ uint8_t smem_raw[];
    const uint32_t sb = (smem_u32(smem_raw) + 1023u) & ~1023u;
    const int tid = threadIdx.x, lane = tid & 31;
    const int warp = __shfl_sync(0xffffffffu, tid >> 5, 0);
    const uint32_t t0 = clk32();
    const int r = blockIdx.x;
    const int half = r & 1, b = r >> 6, cg = r & 63;
    const int g = lane >> 2, t = lane & 3;
    const uint32_t bar_w = sb + SM_BAR, bar_full = bar_w + 32;
    const uint32_t bar_f = bar_full + 8 * NS + 8, bar_m = bar_f + 8, bar_wfree = bar_m + 8, bar_go = bar_wfree + 8, bar_empty = bar_go + 8;
    const uint32_t bar_f2 = bar_empty + 8 * NS, bar_sc = bar_f2 + 8;
    const bool is_ffn = r < NFFN;
    const uint32_t l_row = (lane & 7) + 8 * (lane >> 4);
    const uint32_t l_sel = (lane >> 3) & 1;

    if (warp == 8) {
        const bool el = elect_one();
        const int kv_row0 = (r >> 1) * SK + (SK - WIN);
        u64 pol;
        asm volatile("createpolicy.fractional.L2::evict_first.b64 %0, 1.0;" : "=l"(pol));
        if (el) {
            TSTAMP(0);
            mbar_init(bar_m, 1);
#pragma unroll
            for (int i = 0; i < BURST; i++) mbar_init(bar_w + 8 * i, 1);
            asm volatile("fence.mbarrier_init.release.cluster;" ::: "memory");
            mbar_expect_tx(bar_m, 8192);
            tma2d(sb + SM_P, &tm.Wm, r * 8, 0, bar_m);
            tma2d(sb + SM_P + 4096, &tm.Wm, r * 8, 256, bar_m);
#pragma unroll
            for (int i = 0; i < BURST; i++) {
                mbar_expect_tx(bar_w + 8 * i, TILE);
                if (i < 4) tma2d(sb + i * TILE, &tm.Wq, cg * 64, i * 128, bar_w + 8 * i);
                else       tma2d_ef(sb + i * TILE, &tm.K, half * 64, kv_row0 + (i - 4) * 128, bar_w + 8 * i, pol);
            }
            TSTAMP(8);
#pragma unroll
            for (int i = BURST; i < 2 * NS + 14; i++) if (i != NS + 6) mbar_init(bar_w + 8 * i, ((i < NS + 9 && i != NS + 7) || i >= 2 * NS + 9) ? 1 : 8);
            asm volatile("fence.mbarrier_init.release.cluster;" ::: "memory");
#pragma unroll
            for (int i = 0; i < 4; i++) mbar_expect_tx(bar_sc + 8 * i, 4096);
        }
        __syncwarp();
        cluster_arrive_relaxed();
#pragma unroll 1
        for (int u = BURST; u < 4 + NS + NPF; u++) {
            const uint32_t gb = bar_w + 8 * (u >= BURST + 2 ? u - (BURST - 2) : 2 * (u - BURST) + 1);
            bool rel;
            while (!((rel = mbar_test(bar_empty, 0)) && (u >= 4 + NS || mbar_test(bar_w + 8 * (u - RELD), 0))) && !mbar_test(gb, 0)) check_timeout(t0);
            if (u < 4 + NS) {
                if (el) {
                    mbar_expect_tx(bar_w + 8 * u, TILE);
                    tma2d_ef(sb + u * TILE, &tm.K, half * 64, kv_row0 + (u - 4) * 128, bar_w + 8 * u, pol);
                }
            } else {
                if (rel) break;
                if (el) asm volatile("cp.async.bulk.prefetch.tensor.2d.L2.global.tile [%0, {%1, %2}];"
                                     :: "l"(&tm.K), "r"(half * 64), "r"(kv_row0 + (u - 4) * 128) : "memory");
            }
        }
        int slot = 0, gslot = NS - FSTEADY;
        uint32_t ph = 0, gph = 0;
#pragma unroll 1
        for (int j = NS; j < 36; j++) {
            if (j < 32) mbar_wait(bar_empty + 8 * slot, ph);
            if (FSTEADY < NS && j - FSTEADY < 32) {
                mbar_wait(bar_full + 8 * gslot, gph);
                if (++gslot == NS) { gslot = 0; gph ^= 1u; }
            }
            if (j < 32) {
                if (el) {
                    mbar_expect_tx(bar_full + 8 * slot, TILE);
                    tma2d_ef(sb + SM_RING + slot * TILE, &tm.K, half * 64, kv_row0 + j * 128, bar_full + 8 * slot, pol);
                }
                if (++slot == NS) { slot = 0; ph ^= 1u; }
            } else if (el) {
                const int i = 2 * (j - 32);
                mbar_expect_tx(bar_w + 4 * i, TILE);
                tma2d(sb + SM_W + i * 8192, &tm.Wo, i * 64, cg * 64, bar_w + 4 * i);
                tma2d(sb + SM_W + i * 8192 + 8192, &tm.Wo, i * 64 + 64, cg * 64, bar_w + 4 * i);
            }
        }
        if (el) TSTAMP(17);
        mbar_wait(bar_wfree, 0);
        if (el) {
            mbar_expect_tx(bar_m, 16384);
            tma2d(sb + SM_W + 49152, &tm.Wm16, 2 * DM + r * 16, 0, bar_m);
            tma2d(sb + SM_W + 49152 + 8192, &tm.Wm16, 2 * DM + r * 16, 256, bar_m);
        }
        if (is_ffn) {
            mbar_wait(bar_go, 0);
            if (el) TSTAMP(18);
            if (el) {
                mbar_expect_tx(bar_f, 32768);
#pragma unroll 1
                for (int i = 0; i < 4; i++) tma2d(sb + SM_W + i * 8192, i < 2 ? &tm.W1 : &tm.W3, r * 16, (i & 1) * 256, bar_f);
                mbar_expect_tx(bar_f2, TILE);
#pragma unroll 1
                for (int i = 0; i < 8; i++) tma2d(sb + SM_W + 32768 + i * 2048, &tm.W2, i * 64, r * 16, bar_f2);
            }
        }
        cluster_wait();
        return;
    }

    uint32_t flag;
    asm volatile("ld.relaxed.gpu.global.u32 %0, [%1];" : "=r"(flag) : "l"(&g_epoch) : "memory");

    if (warp == 9) {
        const uint4* xp = reinterpret_cast<const uint4*>(x + b * DM);
        const uint4 xa = __ldg(xp + lane), xb = __ldg(xp + 32 + lane);
        cluster_arrive_relaxed();
        flag += 1u;
        const uint32_t xw[8] = {xa.x, xa.y, xa.z, xa.w, xb.x, xb.y, xb.z, xb.w};
        float s = 0.f;
#pragma unroll
        for (int i = 0; i < 8; i++) s += bf_lo(xw[i]) + bf_hi(xw[i]);
#pragma unroll 1
        for (int o = 16; o > 0; o >>= 1) s += __shfl_xor_sync(0xffffffffu, s, o);
        const float mean = s * (1.0f / DM);
        float m2 = 0.f;
#pragma unroll
        for (int i = 0; i < 8; i++) { const float d0 = bf_lo(xw[i]) - mean, d1 = bf_hi(xw[i]) - mean; m2 += d0 * d0; m2 += d1 * d1; }
#pragma unroll 1
        for (int o = 16; o > 0; o >>= 1) m2 += __shfl_xor_sync(0xffffffffu, m2, o);
        {
            const uint32_t mm = pack_bf16(mean, mean);
            const float rden = ln_rden(m2 * (1.0f / DM));
            sts128(sb + SM_RO + lane * 16, ln_pair(xa.x, mm, rden), ln_pair(xa.y, mm, rden), ln_pair(xa.z, mm, rden), ln_pair(xa.w, mm, rden));
            sts128(sb + SM_RO + 512 + lane * 16, ln_pair(xb.x, mm, rden), ln_pair(xb.y, mm, rden), ln_pair(xb.z, mm, rden), ln_pair(xb.w, mm, rden));
        }
        const int fpos = (cg >> 1) * 8 + 2 * t + (cg & 1);
        if (lane == 0) TSTAMP(19);
        bar_sync<2, 288>();
        {
            float4 v = lds128f(sb + SM_RMOD + g * 64 + t * 16);
#pragma unroll
            for (int o = 4; o < 32; o <<= 1) {
                v.x += __shfl_xor_sync(0xffffffffu, v.x, o); v.y += __shfl_xor_sync(0xffffffffu, v.y, o);
                v.z += __shfl_xor_sync(0xffffffffu, v.z, o); v.w += __shfl_xor_sync(0xffffffffu, v.w, o);
            }
            uint32_t m = g ? pack_bf16(v.y, v.w) : pack_bf16(v.x, v.z);
            if (b) m = bf2_add(m, 0x3f803f80u);
            if (lane < 8) ll_st(&g_ll_m[(g * 6 + b) * 256 + fpos], m, flag);
        }
        if (lane == 0) TSTAMP(1);
        cluster_wait();

        {
            float d[2][4];
#pragma unroll
            for (int i = 0; i < 4; i++) { d[0][i] = d[1][i] = 0.f; }
            mbar_wait(bar_m, 1);
            const uint32_t base = sb + SM_W + 49152 + l_row * 32 + ((l_sel ^ (g & 1)) << 4);
            const uint32_t sa = sb + SM_SILU + (g & 1) * 1024 + t * 4;
#pragma unroll 1
            for (int ks = 0; ks < 32; ks += 2) {
                uint32_t a0[4], a1[4];
                ldsm4t(a0, base + ks * 512);
                ldsm4t(a1, base + ks * 512 + 512);
                mma16816(d[0], a0, lds32(sa + ks * 32), lds32(sa + ks * 32 + 16));
                mma16816(d[1], a1, lds32(sa + ks * 32 + 32), lds32(sa + ks * 32 + 48));
            }
            const uint32_t p0 = pack_bf16(d[0][0] + d[1][0], d[0][2] + d[1][2]), p1 = pack_bf16(d[0][1] + d[1][1], d[0][3] + d[1][3]);
            const uint32_t a0 = __shfl_sync(0xffffffffu, p0, 8 * t), a1 = __shfl_sync(0xffffffffu, p0, 8 * t + 4);
            const uint32_t c0 = __shfl_sync(0xffffffffu, p1, 8 * t), c1 = __shfl_sync(0xffffffffu, p1, 8 * t + 4);
            uint32_t m = __byte_perm((g & 2) ? c0 : a0, (g & 2) ? c1 : a1, (g & 1) ? 0x7632 : 0x5410);
            if ((r >> 5) == 2) m = bf2_add(m, 0x3f803f80u);
            if (lane < 16) ll_st(&g_ll_m[((g >> 1) * 6 + 2) * 256 + r * 8 + 2 * t + (g & 1)], m, flag);
            if (lane == 0) TSTAMP(13);
        }

        bar_sync<4, 288>();
        if (is_ffn) {
            const uint32_t* base = g_ll_r + ((r & 31) * NPP + lane) * 32;
            while (true) {
                uint32_t v0, v1;
                asm volatile("ld.relaxed.gpu.global.u32 %0, [%1];" : "=r"(v0) : "l"(base) : "memory");
                asm volatile("ld.relaxed.gpu.global.u32 %0, [%1];" : "=r"(v1) : "l"(base + 1024) : "memory");
                const int cnt = __popc(__ballot_sync(0xffffffffu, ((v0 ^ flag) & 3u) == 0)) + __popc(__ballot_sync(0xffffffffu, ((v1 ^ flag) & 3u) == 0));
                if (cnt >= THETA + TH_MUL * ((r >> 1) & 7)) break;
                __nanosleep(200);
                check_timeout(t0);
            }
            if (lane == 0) mbar_arrive(bar_go);
        }
        if (r >= 32 && r < 96) return;
        const bool fin = r < 32;
        const int fb = fin ? (lane >> 3) & 1 : (r >> 4) & 1;
        const int col = fin ? r * 16 + (lane >> 4) * 8 + (lane & 7) : (r & 15) * 32 + lane;
        const int wi = (col >> 4) * 8 + (col & 6) + ((col >> 3) & 1);
        u64 gw, xq;
        while (true) {
            asm volatile("ld.relaxed.gpu.global.b64 %0, [%1];" : "=l"(gw) : "l"(&g_ll_m[(fb * 6 + (fin ? 5 : 2)) * 256 + wi]) : "memory");
            if (__all_sync(0xffffffffu, (uint32_t)(gw >> 32) == flag)) break;
            check_timeout(t0);
        }
        if (fin) {
            bar_sync<7, 288>();
            while (true) {
                asm volatile("ld.relaxed.gpu.global.b64 %0, [%1];" : "=l"(xq) : "l"(&g_ll_x[fb * 256 + wi]) : "memory");
                if (__all_sync(0xffffffffu, (uint32_t)(xq >> 32) == flag)) break;
                check_timeout(t0);
            }
        } else {
            xq = __ldg(reinterpret_cast<const uint32_t*>(x + fb * DM) + (col >> 1));
        }
        const float xin = (lane & 1) ? bf_hi((uint32_t)xq) : bf_lo((uint32_t)xq);
        const float gt = (lane & 1) ? bf_hi((uint32_t)gw) : bf_lo((uint32_t)gw);
        sts32f(sb + SM_RMOD + lane * 4, xin + gt);
        bar_sync<6, 288>();
        float v[8];
#pragma unroll
        for (int i = 0; i < 8; i++) v[i] = __uint_as_float(lds32(sb + SM_RQ + i * 128 + lane * 4));
        const float res = xin + bf16r(gt * bf16r(((v[0] + v[1]) + (v[2] + v[3])) + ((v[4] + v[5]) + (v[6] + v[7]))));
        const uint32_t pr = pack_bf16(res, __shfl_down_sync(0xffffffffu, res, 1));
        if (!(lane & 1)) {
            if (fin) reinterpret_cast<uint32_t*>(out)[(fb * DM + col) >> 1] = pr;
            else ll_st(&g_ll_x[fb * 256 + wi], pr, flag);
        }
        TSTAMPD(fin ? 12 : 14, pr);
        if (r == 0 && lane == 0) asm volatile("st.relaxed.gpu.global.u32 [%0], %1;" :: "l"(&g_epoch), "r"(flag) : "memory");
        return;
    }

    const int w = warp;
    {
        const uint32_t* cp = reinterpret_cast<const uint32_t*>(cvec + 64 * w) + lane;
        const uint32_t c0 = __ldg(cp), c1 = __ldg(cp + DM / 2);
        cluster_arrive_relaxed();
        sts32(sb + SM_SILU + w * 128 + lane * 4, pack_bf16(silu_f(bf_lo(c0)), silu_f(bf_hi(c0))));
        sts32(sb + SM_SILU + 1024 + w * 128 + lane * 4, pack_bf16(silu_f(bf_lo(c1)), silu_f(bf_hi(c1))));
        cluster_wait();
        __syncwarp();
        uint32_t sc[8];
#pragma unroll
        for (int i = 0; i < 8; i++) sc[i] = lds32(sb + SM_SILU + (g & 1) * 1024 + w * 128 + i * 16 + t * 4);
        mbar_wait(bar_m, 0);
        if (tid == 0) TSTAMP(15);
        float d[2][4];
        uint32_t a[4][4];
#pragma unroll
        for (int ks = 0; ks < 4; ks++) {
            ldsm2t(a[ks][0], a[ks][2], sb + SM_P + (64 * w + 16 * ks + (lane & 15)) * 16);
            a[ks][1] = a[ks][3] = 0u;
        }
        mma16816z(d[0], a[0], sc[0], sc[1]); mma16816z(d[1], a[1], sc[2], sc[3]);
        mma16816(d[0], a[2], sc[4], sc[5]);  mma16816(d[1], a[3], sc[6], sc[7]);
        if (t == 0) sts64f(sb + SM_RMOD + w * 64 + g * 8, d[0][0] + d[1][0], d[0][1] + d[1][1]);
        bar_sync<2, 288>();
    }
    flag += 1u;

    const uint32_t tr_off = l_row * 128 + ((l_sel ^ (lane & 7)) << 4);
    const uint32_t red_st = (w * 64 + 16 * t + g) * 4;
    uint32_t qf[8];
    {
        const uint32_t lnp = sb + SM_RO + (32 * w + 8 * ((lane >> 2) & 3) + t) * 4;
        const uint32_t ln0 = lds32(lnp), ln1 = lds32(lnp + 16);
        uint4 hv; hv.y = ~flag;
        { const uint32_t c = clk32(); while (clk32() - c < HDELAY) ; }
        ll_poll2(g_ll_m + (b * 6 + (lane >> 4)) * 256 + 32 * w + 2 * (lane & 15), hv, flag, t0);
        uint32_t a[4][4][4];
        mbar_wait(bar_w + 8 * (w >> 1), 0);
        const uint32_t base = sb + SM_W + w * 8192 + tr_off;
#pragma unroll
        for (int j = 0; j < 4; j++)
#pragma unroll
            for (int ks = 0; ks < 4; ks++) ldsm4t(a[ks][j], (base ^ (j << 5)) + ks * 2048);
        if (tid == 0) TSTAMP(2);
        hv.x = bf2_add(bf2_mul(ln0, __shfl_down_sync(0xffffffffu, hv.x, 16)), hv.x);
        hv.z = bf2_add(bf2_mul(ln1, __shfl_down_sync(0xffffffffu, hv.z, 16)), hv.z);
        float d[4][4];
#pragma unroll
        for (int ks = 0; ks < 4; ks++) {
            const uint32_t b0 = __shfl_sync(0xffffffffu, hv.x, 4 * ks + t);
            const uint32_t b1 = __shfl_sync(0xffffffffu, hv.z, 4 * ks + t);
#pragma unroll
            for (int j = 0; j < 4; j++) { if (ks == 0) mma16816z(d[j], a[ks][j], b0, b1); else mma16816(d[j], a[ks][j], b0, b1); }
        }
        sts32f(sb + SM_RQ + red_st, sel4(t, d[0][0], d[1][0], d[2][0], d[3][0]));
        sts32f(sb + SM_RQ + red_st + 32, sel4(t, d[0][2], d[1][2], d[2][2], d[3][2]));
        bar_sync<1, 256>();
        float q0 = 0.f, q1 = 0.f;
#pragma unroll
        for (int i = 0; i < 8; i++) { float2 v = lds64f(sb + SM_RQ + i * 256 + lane * 8); q0 += v.x; q1 += v.y; }
        const uint32_t qp = pack_bf16(q0, q1);
#pragma unroll
        for (int i = 0; i < 8; i++) qf[i] = __shfl_sync(0xffffffffu, qp, 4 * i + t);
        if (tid == 0) TSTAMP(3);
    }

    int slot = 0;
    uint32_t ph = 0;
    const float ZERO_P = -92.93f;
    const uint32_t lst = sb + SM_SCO;
    float m_a = 0.f, sum_a = 0.f;
    int nst_a = 0;
    {
        const uint32_t k_off = sb + SM_RING + (16 * w + (lane & 7) + 8 * l_sel) * 128 + (((lane >> 4) ^ (lane & 7)) << 4);
        uint32_t rem_sc, rem_bar;
        asm("mapa.shared::cluster.u32 %0, %1, %2;" : "=r"(rem_sc) : "r"(sb + SM_SCR), "r"(half ^ 1));
        asm("mapa.shared::cluster.u32 %0, %1, %2;" : "=r"(rem_bar) : "r"(bar_sc), "r"(half ^ 1));
        const uint32_t s_off = (16 * w + 8 * (t & 1) + g) * 4;
        float u[3][4];
#pragma unroll
        for (int j = 0; j < 4; j++) {
#pragma unroll 1
            for (int kt = (j ? 8 * j + KLAG : 0); kt < (j < 3 ? 8 * j + 8 + KLAG : 32); kt++) {
                mbar_wait(bar_full + 8 * slot, ph);
                if (tid == 0) THIST(8);
                const uint32_t base = k_off + slot * TILE;
                uint32_t a[4][4];
#pragma unroll
                for (int ks = 0; ks < 4; ks++) ldsm4(a[ks], base ^ (ks << 5));
                float d0[4], d1[4];
                mma16816z(d0, a[0], qf[0], qf[1]); mma16816z(d1, a[1], qf[2], qf[3]);
                mma16816(d0, a[2], qf[4], qf[5]); mma16816(d1, a[3], qf[6], qf[7]);
                if (lane == 0) mbar_arrive(bar_empty + 8 * slot);
                const float v = (t & 1) ? d0[2] + d1[2] : d0[0] + d1[0];
                if (t < 2) sts32f(sb + SM_SCO + kt * 512 + s_off, v);
                else asm volatile("st.async.weak.shared::cluster.mbarrier::complete_tx::bytes.f32 [%0], %1, [%2];"
                                  :: "r"(rem_sc + kt * 512 + s_off), "f"(v), "r"(rem_bar + (kt >> 3) * 8) : "memory");
                if (++slot == NS) { slot = 0; ph ^= 1; }
            }
            if (j < 3) {
                bar_sync<1, 256>();
                mbar_wait_cluster(bar_sc + 8 * j, 0);
                const float4 p = lds128f(lst + tid * 16 + j * 4096), v = lds128f(lst + tid * 16 + j * 4096 + 16384);
                u[j][0] = score_round(p.x + v.x); u[j][1] = score_round(p.y + v.y);
                u[j][2] = score_round(p.z + v.z); u[j][3] = score_round(p.w + v.w);
            }
            if (j == 2) {
                float mx = -3.0e38f;
#pragma unroll
                for (int i = 0; i < 3; i++) mx = fmaxf(fmaxf(mx, fmaxf(u[i][0], u[i][1])), fmaxf(u[i][2], u[i][3]));
                mx = warp_max(mx);
                if (lane == 0) sts32f(sb + SM_SMAX + w * 4, mx);
                bar_sync<1, 256>();
                {
                    const float4 p = lds128f(sb + SM_SMAX), v = lds128f(sb + SM_SMAX + 16);
                    m_a = fmaxf(fmaxf(fmaxf(p.x, p.y), fmaxf(p.z, p.w)), fmaxf(fmaxf(v.x, v.y), fmaxf(v.z, v.w)));
                }
                uint32_t keep = 0, cnt = 0;
#pragma unroll
                for (int i = 0; i < 3; i++)
#pragma unroll
                    for (int e = 0; e < 4; e++) {
                        const float dlt = u[i][e] - m_a;
                        if (!(dlt < ZERO_P)) { keep |= 1u << (4 * i + e); cnt += 1u << (8 * i); }
                        u[i][e] = ex2_sub(dlt * LOG2E);
                        sum_a += u[i][e];
                    }
                uint32_t inc = cnt;
#pragma unroll
                for (int o = 1; o < 32; o <<= 1) {
                    const uint32_t v = __shfl_up_sync(0xffffffffu, inc, o);
                    if (lane >= o) inc += v;
                }
                if (lane == 31) sts32(sb + SM_SCNT + w * 4, inc);
                bar_sync<1, 256>();
                uint32_t lo = 0, hi = 0, tlo = 0, thi = 0;
                {
                    uint32_t c[8];
                    lds128(c, sb + SM_SCNT); lds128(c + 4, sb + SM_SCNT + 16);
#pragma unroll
                    for (int i = 0; i < 8; i++) {
                        const uint32_t cl = c[i] & 0x00ff00ffu, ch = (c[i] >> 8) & 0xffu;
                        tlo += cl; thi += ch;
                        if (i < w) { lo += cl; hi += ch; }
                    }
                }
                const uint32_t exc = inc - cnt;
                const uint32_t n0 = tlo & 0xffffu, n_a = n0 + thi + (tlo >> 16);
#pragma unroll
                for (int i = 0; i < 3; i++) {
                    const uint32_t pos = i == 0 ? (lo & 0xffffu) : i == 1 ? n0 + hi : n0 + thi + (lo >> 16);
                    uint32_t a = lst + 4 * (pos + ((exc >> (8 * i)) & 0xffu));
#pragma unroll
                    for (int e = 0; e < 4; e++)
                        if (keep & (1u << (4 * i + e))) { sts32f(a, u[i][e]); sts32(a + 16384, (uint32_t)(1024 * i + 4 * tid + e) * 256u); a += 4; }
                }
                nst_a = (int)(n_a + 15) >> 4;
                if (tid < 16 && n_a + tid < 16u * nst_a) { sts32(lst + 4 * (n_a + tid), 0u); sts32(lst + 16384 + 4 * (n_a + tid), (WIN - 1) * 256u); }
            }
        }
    }
    if (tid == 0) TSTAMP(4);

    float o[4][4];
#pragma unroll
    for (int j = 0; j < 4; j++) { o[j][0] = o[j][1] = o[j][2] = o[j][3] = 0.f; }
    uint32_t wo_a[4][4][4];
    const int bb = lane >> 4;
    const u64* msrc = g_ll_m + (bb * 6 + 3) * 256 + 32 * w + 2 * (lane & 15);
    uint4 mc, ms;
    {
        const int dtot = max(1, min(min(8 * (VD - 1), nst_a), (nst_a * (4 * VDEPTH / 3) + 128) >> 8));
        const int dd = (dtot + 7 - w) >> 3;
        const int wrap = dtot - 8 * (dd - 1);
        u64 pol;
        asm volatile("createpolicy.fractional.L2::evict_first.b64 %0, 1.0;" : "=l"(pol));
        const char* vsrc[4];
        {
            const char* vb = reinterpret_cast<const char*>(vcache) + ((size_t)(r >> 1) * SK + (SK - WIN)) * 256 + half * 128;
            const uint32_t x0 = ((lane & 7) ^ ((lane >> 1) & 4)) << 4;
#pragma unroll
            for (int j = 0; j < 4; j++) { vsrc[j] = vb + (x0 ^ (j << 4)); asm volatile("" : "+l"(vsrc[j])); }
        }
        const uint32_t ring = sb + SM_RING + w * (VD * 2048);
        uint32_t vdst = ring + (lane >> 3) * 512 + (lane & 7) * 16, lrow = lst + (lane >> 3) * 16;
        asm volatile("" : "+r"(vdst), "+r"(lrow));
        int ik = 0, ist = w, id = 0, isl = 0;
        float sc_a = 1.0f, sc_b = 1.0f;
        const char* nsrc[4];
        float npr[4];
        auto prep = [&]() {
            uint32_t en[4];
            lds128(en, lrow + 16384 + ist * 64);
            const float4 ev = lds128f(lrow + ist * 64);
            const float f = ist < nst_a ? sc_a : sc_b;
            npr[0] = ev.x * f; npr[1] = ev.y * f; npr[2] = ev.z * f; npr[3] = ev.w * f;
#pragma unroll
            for (int j = 0; j < 4; j++) nsrc[j] = vsrc[j] + en[j];
        };
        auto fire = [&]() {
#pragma unroll
            for (int j = 0; j < 4; j++)
                asm volatile("cp.async.cg.shared.global.L2::cache_hint [%0], [%1], 16, %2, %3;"
                             :: "r"(vdst + isl * 2048 + j * 128), "l"(nsrc[j]), "r"(npr[j] <= 0x1p-134f ? 0 : 16), "l"(pol) : "memory");
            asm volatile("cp.async.commit_group;" ::: "memory");
            ik++;
            if (++id == dd) { id = 0; ist += wrap; } else ist += 8;
            if (++isl == VD) isl = 0;
        };
        bar_sync<1, 256>();
#pragma unroll 1
        while (ik < dd) { prep(); fire(); }
        if (tid == 0) TSTAMP(20);
        int nst;
        {
            mbar_wait_cluster(bar_sc + 24, 0);
            if (tid == 0) TSTAMP(21);
            const float4 p = lds128f(lst + tid * 16 + 12288), v = lds128f(lst + tid * 16 + 12288 + 16384);
            float u[4] = {score_round(p.x + v.x), score_round(p.y + v.y), score_round(p.z + v.z), score_round(p.w + v.w)};
            float mx = warp_max(fmaxf(fmaxf(u[0], u[1]), fmaxf(u[2], u[3])));
            if (lane == 0) sts32f(sb + SM_SMAX + w * 4, mx);
            bar_sync<1, 256>();
            {
                const float4 p2 = lds128f(sb + SM_SMAX), v2 = lds128f(sb + SM_SMAX + 16);
                mx = fmaxf(m_a, fmaxf(fmaxf(fmaxf(p2.x, p2.y), fmaxf(p2.z, p2.w)), fmaxf(fmaxf(v2.x, v2.y), fmaxf(v2.z, v2.w))));
            }
            if (tid == 0) TSTAMPD(22, __float_as_uint(mx));
            const float ca = ex2_sub((m_a - mx) * LOG2E);
            float sum = sum_a * ca;
            uint32_t keep = 0, cnt = 0;
#pragma unroll
            for (int e = 0; e < 4; e++) {
                const float dlt = u[e] - mx;
                if (!(dlt < ZERO_P)) { keep |= 1u << e; cnt++; }
                u[e] = ex2_sub(dlt * LOG2E);
                sum += u[e];
            }
            uint32_t inc = cnt;
#pragma unroll
            for (int of = 1; of < 32; of <<= 1) {
                const uint32_t vv = __shfl_up_sync(0xffffffffu, inc, of);
                if (lane >= of) inc += vv;
                sum += __shfl_xor_sync(0xffffffffu, sum, of);
            }
            if (lane == 31) { sts32f(sb + SM_SSUM + w * 4, sum); sts32(sb + SM_SCNT + w * 4, inc); }
            bar_sync<1, 256>();
            {
                const float4 p2 = lds128f(sb + SM_SSUM), v2 = lds128f(sb + SM_SSUM + 16);
                sum = ((p2.x + p2.y) + (p2.z + p2.w)) + ((v2.x + v2.y) + (v2.z + v2.w));
            }
            if (tid == 0) TSTAMPD(28, __float_as_uint(sum));
            uint32_t pos = 16 * nst_a, n = pos;
            {
                uint32_t c[8];
                lds128(c, sb + SM_SCNT); lds128(c + 4, sb + SM_SCNT + 16);
#pragma unroll
                for (int i = 0; i < 8; i++) { n += c[i]; if (i < w) pos += c[i]; }
            }
            uint32_t a = lst + 4 * (pos + inc - cnt);
#pragma unroll
            for (int e = 0; e < 4; e++)
                if (keep & (1u << e)) { sts32f(a, u[e]); sts32(a + 16384, (uint32_t)(3072 + 4 * tid + e) * 256u); a += 4; }
            nst = (int)(n + 15) >> 4;
            if (tid < 16 && n + tid < 16u * nst) { sts32(lst + 4 * (n + tid), 0u); sts32(lst + 16384 + 4 * (n + tid), (WIN - 1) * 256u); }
            sc_b = rcp_fast(sum);
            sc_a = ca * sc_b;
            bar_sync<1, 256>();
        }
        if (tid == 0) TSTAMP(5);
        const int rounds = nst / dtot;
        const int nw = rounds * dd + max(0, (nst - rounds * dtot + 7 - w) >> 3);
        {
            uint32_t* dst = g_ll_r + ((b * 16 + 2 * w) * NPP + cg) * 32 + t * 8 + g;
            tag_st(dst, 0.f, (flag & 3u) ^ 2u); tag_st(dst + NPP * 32, 0.f, (flag & 3u) ^ 2u);
        }
        bool polled = false;
        int ck = 0, cst = w, cd = 0, csl = 0;
#pragma unroll 1
        do {
            if (!polled && ik + POLL_REM >= nw) {
                polled = true;
                bar_arrive<4, 288>();
                if (is_ffn) { ll_ld2(msrc, ms); ll_ld2(msrc + 256, mc); }
            }
            if (ck < nw) {
                const bool more = ik < nw && ik - ck <= dd;
                if (more) prep();
                const float2 e0 = lds64f(lst + cst * 64 + t * 8), e1 = lds64f(lst + cst * 64 + 32 + t * 8);
                const float sc = cst < nst_a ? sc_a : sc_b;
                const uint32_t b0 = pack_bf16(e0.x * sc, e0.y * sc), b1 = pack_bf16(e1.x * sc, e1.y * sc);
                switch (ik - ck) {
                    case 1: asm volatile("cp.async.wait_group 0;" ::: "memory"); break;
                    case 2: asm volatile("cp.async.wait_group 1;" ::: "memory"); break;
                    case 3: asm volatile("cp.async.wait_group 2;" ::: "memory"); break;
                    case 4: asm volatile("cp.async.wait_group 3;" ::: "memory"); break;
                    case 5: asm volatile("cp.async.wait_group 4;" ::: "memory"); break;
                    case 6: asm volatile("cp.async.wait_group 5;" ::: "memory"); break;
                    default: asm volatile("cp.async.wait_group 6;" ::: "memory"); break;
                }
                __syncwarp();
                if (more) fire();
                if (lane == 0) THIST(1);
                const uint32_t base = ring + csl * 2048 + tr_off;
                uint32_t a[4][4];
#pragma unroll
                for (int j = 0; j < 4; j++) ldsm4t(a[j], base ^ (j << 5));
#pragma unroll
                for (int j = 0; j < 4; j++) mma16816(o[j], a[j], b0, b1);
                if (++cd == dd) { cd = 0; cst += wrap; } else cst += 8;
                if (++csl == VD) csl = 0;
            }
            if (ck == 0) {
                mbar_wait(bar_w + 8 * (w >> 1), 1);
#pragma unroll
                for (int j = 0; j < 4; j++)
#pragma unroll
                    for (int ks = 0; ks < 4; ks++) ldsm4t(wo_a[ks][j], ((sb + SM_W + w * 8192 + tr_off) ^ (j << 5)) + ks * 2048);
                __syncwarp();
                if (lane == 0) mbar_arrive(bar_wfree);
            }
        } while (++ck < nw);
    }
    TSTAMPD(6, __float_as_uint(o[3][0]));

    const uint32_t tag = flag & 3u;
    {
        sts32f(sb + SM_RO + red_st, sel4(t, o[0][0], o[1][0], o[2][0], o[3][0]));
        sts32f(sb + SM_RO + red_st + 32, sel4(t, o[0][2], o[1][2], o[2][2], o[3][2]));
        uint32_t* dst = g_ll_r + ((b * 16 + 2 * w) * NPP + cg) * 32 + t * 8 + g;
        bar_sync<1, 256>();
        float2 v[8];
#pragma unroll
        for (int i = 0; i < 8; i++) v[i] = lds64f(sb + SM_RO + i * 256 + lane * 8);
        const float o0 = ((v[0].x + v[1].x) + (v[2].x + v[3].x)) + ((v[4].x + v[5].x) + (v[6].x + v[7].x));
        const float o1 = ((v[0].y + v[1].y) + (v[2].y + v[3].y)) + ((v[4].y + v[5].y) + (v[6].y + v[7].y));
        const uint32_t op = pack_bf16(o0, o1);
        uint32_t bf[8];
#pragma unroll
        for (int i = 0; i < 8; i++) bf[i] = __shfl_sync(0xffffffffu, op, 4 * i + t);
        float d[2][4][4];
#pragma unroll
        for (int ks = 0; ks < 4; ks++)
#pragma unroll
            for (int j = 0; j < 4; j++) {
                if (ks < 2) mma16816z(d[ks][j], wo_a[ks][j], bf[2 * ks], bf[2 * ks + 1]);
                else        mma16816(d[ks & 1][j], wo_a[ks][j], bf[2 * ks], bf[2 * ks + 1]);
            }
        const float r0 = sel4(t, d[0][0][0], d[0][0][2], d[0][1][0], d[0][1][2]) + sel4(t, d[1][0][0], d[1][0][2], d[1][1][0], d[1][1][2]);
        const float r1 = sel4(t, d[0][2][0], d[0][2][2], d[0][3][0], d[0][3][2]) + sel4(t, d[1][2][0], d[1][2][2], d[1][3][0], d[1][3][2]);
        tag_st(dst, r0, tag);
        tag_st(dst + NPP * 32, r1, tag);
        TSTAMPD(23, op);
        TSTAMPD(7, __float_as_uint(r1));
    }
    auto gather = [&](int box, int per, int n) {
        const uint32_t* src = g_ll_r + (box * NPP + per * w) * 32 + lane;
        float s0, s1;
        while (true) {
            uint32_t v[11], bad = 0;
#pragma unroll
            for (int i = 0; i < 11; i++) {
                v[i] = tag;
                if (i < 8 || i < n) asm volatile("ld.relaxed.gpu.global.u32 %0, [%1];" : "=r"(v[i]) : "l"(src + i * 32) : "memory");
            }
#pragma unroll
            for (int i = 0; i < 11; i++) {
                v[i] ^= tag; bad |= v[i];
                if (i == 0) s0 = __uint_as_float(v[i]); else if (i == 1) s1 = __uint_as_float(v[i]);
                else if (i & 1) s1 += __uint_as_float(v[i]); else s0 += __uint_as_float(v[i]);
            }
            if (__all_sync(0xffffffffu, (bad & 3u) == 0)) break;
            check_timeout(t0);
        }
        sts32f(sb + SM_RQ + w * 128 + lane * 4, s0 + s1);
        TSTAMPD(r < 32 ? 26 : 27, __float_as_uint(s0));
        bar_arrive<6, 288>();
    };
#define DUMPH() do { } while (0)
    if (!is_ffn) {
        if (r >= 96) gather(r - 96, 8, 8);
        DUMPH();
        return;
    }

    uint32_t f_a[2][4][4], w2_a[4][4];
    {
        mbar_wait(bar_f, 0);
        const uint32_t fb = sb + SM_W + l_sel * 16384 + (64 * w + l_row) * 32 + ((g & 1) << 4);
#pragma unroll
        for (int j = 0; j < 2; j++)
#pragma unroll
            for (int ks = 0; ks < 4; ks++) ldsm4t(f_a[j][ks], (fb ^ (j << 4)) + ks * 512);
        mbar_wait(bar_f2, 0);
#pragma unroll
        for (int j = 0; j < 4; j++) ldsm4t(w2_a[j], (sb + SM_W + 32768 + w * 2048 + tr_off) ^ (j << 5));
    }
    {
        while (!__all_sync(0xffffffffu, ms.y == flag && ms.w == flag && mc.y == flag && mc.w == flag)) {
            ll_ld2(msrc, ms); ll_ld2(msrc + 256, mc); check_timeout(t0);
        }
        uint32_t* dst = g_ll_r + ((32 + 4 * w) * NPP + r) * 32 + t * 8 + g;
#pragma unroll
        for (int j = 0; j < 4; j++) tag_st(dst + j * NPP * 32, 0.f, tag ^ 2u);
        auto gemv = [&](uint32_t p0, uint32_t p1, float (&acc)[4]) {
            float d[2][4][4];
#pragma unroll
            for (int ks = 0; ks < 4; ks++) {
                const uint32_t b0 = __shfl_sync(0xffffffffu, p0, 16 * (g & 1) + 4 * ks + t);
                const uint32_t b1 = __shfl_sync(0xffffffffu, p1, 16 * (g & 1) + 4 * ks + t);
#pragma unroll
                for (int j = 0; j < 2; j++) mma16816z(d[j][ks], f_a[j][ks], b0, b1);
            }
#pragma unroll
            for (int i = 0; i < 4; i++) {
                const float u0 = (d[0][0][i] + d[0][1][i]) + (d[0][2][i] + d[0][3][i]);
                const float u1 = (d[1][0][i] + d[1][1][i]) + (d[1][2][i] + d[1][3][i]);
                acc[i] = (t & 1) ? u1 : u0;
            }
        };
        auto sum8 = [&](uint32_t base) {
            float2 v[8];
#pragma unroll
            for (int i = 0; i < 8; i++) v[i] = lds64f(base + i * 256 + (lane & 15) * 16 + bb * 8);
            return make_float2(((v[0].x + v[1].x) + (v[2].x + v[3].x)) + ((v[4].x + v[5].x) + (v[6].x + v[7].x)),
                               ((v[0].y + v[1].y) + (v[2].y + v[3].y)) + ((v[4].y + v[5].y) + (v[6].y + v[7].y)));
        };
        const uint32_t pst = w * 256 + (8 * t + g) * 16;
        float cw[4];
#pragma unroll 1
        for (int i = 0; i < 2; i++) {
            gemv(i ? mc.x : ms.x, i ? mc.z : ms.z, cw);
            if (t < 2) sts128f(sb + SM_P + i * 2048 + pst, cw[0], cw[2], cw[1], cw[3]);
        }
        bar_sync<1, 256>();
        const float2 St = sum8(sb + SM_P), Ct = sum8(sb + SM_P + 2048);
        const float c0 = bf_lo(mc.x), c1 = bf_hi(mc.x), c2 = bf_lo(mc.z), c3 = bf_hi(mc.z);
        TSTAMPD(24, __float_as_uint(Ct.x));
        uint4 xv;
        xv.y = ~flag;
        ll_poll2(g_ll_x + bb * 256 + 32 * w + 2 * (lane & 15), xv, flag, t0);
        TSTAMPD(9, xv.x);
        if (r < 32) bar_arrive<7, 288>();
        const float pv0 = bf_lo(__shfl_sync(0xffffffffu, xv.x, 0)), pv1 = bf_lo(__shfl_sync(0xffffffffu, xv.x, 16));
        const float piv = bb ? pv1 : pv0;
        const float e0 = bf_lo(xv.x) - piv, e1 = bf_hi(xv.x) - piv, e2 = bf_lo(xv.z) - piv, e3 = bf_hi(xv.z) - piv;
        float acc[4];
        gemv(pack_bf16(e0 * c0, e1 * c1), pack_bf16(e2 * c2, e3 * c3), acc);
        float s1 = (e0 + e1) + (e2 + e3), s2 = (e0 * e0 + e1 * e1) + (e2 * e2 + e3 * e3);
#pragma unroll
        for (int of = 1; of < 16; of <<= 1) { s1 += __shfl_xor_sync(0xffffffffu, s1, of); s2 += __shfl_xor_sync(0xffffffffu, s2, of); }
        if ((lane & 15) == 0) sts64f(sb + SM_STAT + bb * 64 + w * 8, piv + s1 * (1.0f / 64.0f), s2 - s1 * s1 * (1.0f / 64.0f));
        if (t < 2) sts128f(sb + SM_RGU + pst, acc[0] + pv0 * cw[0], acc[2] + pv0 * cw[2], acc[1] + pv1 * cw[1], acc[3] + pv1 * cw[3]);
        bar_sync<1, 256>();
        float4 st[4];
#pragma unroll
        for (int i = 0; i < 4; i++) st[i] = lds128f(sb + SM_STAT + bb * 64 + i * 16);
        const float2 P = sum8(sb + SM_RGU);
        const float mean = (((st[0].x + st[0].z) + (st[1].x + st[1].z)) + ((st[2].x + st[2].z) + (st[3].x + st[3].z))) * 0.125f;
        const float M2 = ((st[0].y + st[0].w) + (st[1].y + st[1].w)) + ((st[2].y + st[2].w) + (st[3].y + st[3].w));
        float dv[4];
#pragma unroll
        for (int i = 0; i < 4; i++) { const float d0 = st[i].x - mean, d1 = st[i].z - mean; dv[i] = d0 * d0 + d1 * d1; }
        const float rden = ln_rden(fmaxf(M2 * (1.0f / DM) + ((dv[0] + dv[1]) + (dv[2] + dv[3])) * 0.125f, 0.f));
        const float mb = bf16r(mean);
        const float gate = bf16r(rden * (P.x - mb * Ct.x) + St.x), up = bf16r(rden * (P.y - mb * Ct.y) + St.y);
        TSTAMPD(10, __float_as_uint(gate));
        const float hh = bf16r(silu_f(gate)) * up;
        const int sl0 = 16 * (g & 1) + 2 * t;
        const float h0 = __shfl_sync(0xffffffffu, hh, sl0), h1 = __shfl_sync(0xffffffffu, hh, sl0 + 1);
        const float h8 = __shfl_sync(0xffffffffu, hh, sl0 + 8), h9 = __shfl_sync(0xffffffffu, hh, sl0 + 9);
        const uint32_t b0 = pack_bf16(h0, h1), b1 = pack_bf16(h8, h9);
        float f[4][4];
#pragma unroll
        for (int j = 0; j < 4; j++) mma16816z(f[j], w2_a[j], b0, b1);
#pragma unroll
        for (int j = 0; j < 4; j++) tag_st(dst + j * NPP * 32, sel4(t, f[j][0], f[j][1], f[j][2], f[j][3]), tag);
        TSTAMPD(11, __float_as_uint(f[3][3]));
        if (r < 32) {
            { const uint32_t c = clk32(); while (clk32() - c < XDELAY) ; }
            gather(32 + r, 11, w < 7 ? 11 : NFFN - 77);
        }
        DUMPH();
    }
}

typedef CUresult (*EncodeFn)(CUtensorMap*, CUtensorMapDataType, cuuint32_t, void*, const cuuint64_t*, const cuuint64_t*,
                             const cuuint32_t*, const cuuint32_t*, CUtensorMapInterleave, CUtensorMapSwizzle,
                             CUtensorMapL2promotion, CUtensorMapFloatOOBfill);

void make_map(EncodeFn enc, CUtensorMap* tm, const void* ptr, uint64_t cols, uint64_t rows, uint32_t box_cols,
              uint32_t box_rows, CUtensorMapSwizzle sw, CUtensorMapL2promotion promo) {
    cuuint64_t gd[2] = {cols, rows};
    cuuint64_t gs[1] = {cols * 2};
    cuuint32_t box[2] = {box_cols, box_rows};
    cuuint32_t es[2] = {1, 1};
    enc(tm, CU_TENSOR_MAP_DATA_TYPE_BFLOAT16, 2, const_cast<void*>(ptr), gd, gs, box, es, CU_TENSOR_MAP_INTERLEAVE_NONE,
        sw, promo, CU_TENSOR_MAP_FLOAT_OOB_FILL_NONE);
}

}

extern "C" void kernel_launch(void* const* d_in, const int* in_sizes, int n_in, void* d_out, int out_size) {
    (void)in_sizes; (void)n_in; (void)out_size;
    static EncodeFn enc = nullptr;
    if (!enc) {
        cudaDriverEntryPointQueryResult qr;
        cudaGetDriverEntryPoint("cuTensorMapEncodeTiled", (void**)&enc, cudaEnableDefault, &qr);
        cudaFuncSetAttribute(fused_decode_kernel, cudaFuncAttributeMaxDynamicSharedMemorySize, SMEM_BYTES);
    }
    Maps tm;
    const CUtensorMapSwizzle S128 = CU_TENSOR_MAP_SWIZZLE_128B;
    const CUtensorMapL2promotion P256 = CU_TENSOR_MAP_L2_PROMOTION_L2_256B, P128 = CU_TENSOR_MAP_L2_PROMOTION_L2_128B;
    make_map(enc, &tm.K, d_in[1], 128, (uint64_t)64 * SK, 64, 128, S128, P128);
    make_map(enc, &tm.Wq, d_in[3], 4096, 512, 64, 128, S128, P256);
    make_map(enc, &tm.Wo, d_in[4], 512, 4096, 64, 64, S128, P256);
    make_map(enc, &tm.W2, d_in[8], 512, FF, 64, 16, S128, P256);
    make_map(enc, &tm.Wm, d_in[10], 6 * DM, 512, 8, 256, CU_TENSOR_MAP_SWIZZLE_NONE, P128);
    make_map(enc, &tm.Wm16, d_in[10], 6 * DM, 512, 16, 256, CU_TENSOR_MAP_SWIZZLE_32B, P128);
    make_map(enc, &tm.W1, d_in[6], FF, 512, 16, 256, CU_TENSOR_MAP_SWIZZLE_32B, P128);
    make_map(enc, &tm.W3, d_in[7], FF, 512, 16, 256, CU_TENSOR_MAP_SWIZZLE_32B, P128);
    fused_decode_kernel<<<NCTA, NTHREADS, SMEM_BYTES>>>(
        (const bf16*)d_in[0], (const bf16*)d_in[9], (const bf16*)d_in[2], (bf16*)d_out, tm);
}
```
